```python
import torch

def _softmax(x, axis=-1):
    return torch.softmax(x, dim=axis)
def _gelu(x):
    return torch.nn.functional.gelu(x, approximate="tanh")
def _silu(x):
    return torch.nn.functional.silu(x)
def _sigmoid(x):
    return torch.sigmoid(x)
def _layernorm(x, axis=-1, eps=1e-5):
    m = x.mean(dim=axis, keepdim=True)
    v = x.var(dim=axis, keepdim=True, unbiased=False)
    return (x - m) / torch.sqrt(v + eps)
def _scatter_add(tgt, idx, src, axis=0):
    return tgt.clone().index_add_(axis, idx, src)
def _segment_sum(src, seg, n):
    out = torch.zeros((n,) + src.shape[1:], dtype=src.dtype)
    return out.index_add_(0, seg, src)
def _pad(x, pw):
    flat = tuple(v for pair in reversed(pw) for v in pair)
    return torch.nn.functional.pad(x, flat)

kernel_name = 'standalone__kv_cache_quant_int4_int2_kv_with_per_channel_or_per_token_scales__prompt'

def setup_inputs():

    _w = (lambda a: (lambda t: t.to(torch.bfloat16) if t.is_floating_point() else t)(torch.as_tensor(a)))
    B = 1
    Sq = 2048
    Skv = 2048
    Hq = 32
    Hkv = 4
    Dh = 128
    bits = 4
    G = 128
    if G <= 0 or G >= Skv:
        G = max(1, Skv // 2)
    Skv = (Skv // G) * G
    ngk = Skv // G
    qmax = (1 << bits) - 1
    return {
        "q": _w((lambda *s: torch.randn(*s, dtype=torch.bfloat16) * 1.6)(B, Hq, Sq, Dh)),
        "qk": _w(torch.randint(0, qmax + 1, (B, Hkv, Skv, Dh)).to(torch.int32)),
        "qv": _w(torch.randint(0, qmax + 1, (B, Hkv, Skv, Dh)).to(torch.int32)),
        "k_scales": _w(torch.abs((lambda *s: torch.randn(*s, dtype=torch.bfloat16) * 1.6)(B, Hkv, ngk, Dh)) * 0.05 + 0.02),
        "k_zeros": _w((lambda *s: torch.randn(*s, dtype=torch.bfloat16) * 1.6)(B, Hkv, ngk, Dh) + float(qmax) / 2.0),
        "v_scales": _w(torch.abs((lambda *s: torch.randn(*s, dtype=torch.bfloat16) * 0.05)(B, Hkv, Skv, 1)) * 0.05 + 0.02),
        "v_zeros": _w((lambda *s: torch.randn(*s, dtype=torch.bfloat16) * 0.05)(B, Hkv, Skv, 1) + float(qmax) / 2.0),
    }

def reference(q, qk, qv, k_scales, k_zeros, v_scales, v_zeros):
    B, Hq, Sq, Dh = q.shape
    Hkv, Skv = qk.shape[1], qk.shape[2]
    ngk = k_scales.shape[2]
    G = Skv // ngk
    ks = (lambda x, n, axis: torch.repeat_interleave(x, n, dim=axis))(k_scales, G, axis=2)
    kz = (lambda x, n, axis: torch.repeat_interleave(x, n, dim=axis))(k_zeros, G, axis=2)
    k = ((lambda x, dt: x.to(dt))(qk, q.dtype) - kz) * ks
    v = ((lambda x, dt: x.to(dt))(qv, q.dtype) - v_zeros) * v_scales
    rep = Hq // Hkv
    if rep > 1:
        k = (lambda x, n, axis: torch.repeat_interleave(x, n, dim=axis))(k, rep, axis=1)
        v = (lambda x, n, axis: torch.repeat_interleave(x, n, dim=axis))(v, rep, axis=1)
    scale = float(Dh) ** -0.5
    logits = torch.einsum("bhqd,bhkd->bhqk", q, k) * scale
    p = _softmax(logits, axis=-1)
    o = torch.einsum("bhqk,bhkd->bhqd", p, v)
    return o
```

```cpp
#include <cuda_runtime.h>
#include <cuda.h>
#include <cuda_bf16.h>
#include <stdint.h>

namespace {

constexpr int HQ = 32, HKV = 4, SEQ = 2048, DH = 128;
constexpr int BLK = 128;
constexpr int NBLK = SEQ / BLK;
constexpr int TILE_BYTES = BLK * DH * 2;
constexpr int ROWS = HQ * SEQ;
constexpr int TILE_M = 128;
constexpr int NTILES = ROWS / TILE_M;
constexpr int TILES_PER_KVH = NTILES / HKV;
constexpr int NSLOT = 6;
constexpr int SMEM_BYTES = (NSLOT + 1) * TILE_BYTES + 1024 + 256 + 1024;

constexpr float FAST_BOUND2 = 2500.0f;
constexpr uint32_t VMAX_LO = 0x2B800000u;
constexpr uint32_t VMAX_HI = 0x5D800000u;

__device__ __align__(1024) uint8_t g_kv[2 * HKV * NBLK * TILE_BYTES];
__device__ uint32_t g_ready[HKV];
__device__ uint32_t g_kn2[HKV];
__device__ uint32_t g_vmax[HKV];
__device__ uint32_t g_done;

#define TRACE_PT(idx)
#define TR2(k)
#define TR3(role, k)
#define TR3C(k)
__device__ __forceinline__ uint32_t smem_u32(const void* p) { return (uint32_t)__cvta_generic_to_shared(p); }

__device__ __forceinline__ uint32_t pack_bf16(float lo, float hi) {
  uint32_t r;
  asm("cvt.rn.bf16x2.f32 %0, %1, %2;" : "=r"(r) : "f"(hi), "f"(lo));
  return r;
}
__device__ __forceinline__ float bf_lo(uint32_t v) { return __uint_as_float(v << 16); }
__device__ __forceinline__ float bf_hi(uint32_t v) { return __uint_as_float(v & 0xffff0000u); }
__device__ __forceinline__ uint32_t bsub2(uint32_t a, uint32_t b) {
  uint32_t r; asm("sub.rn.bf16x2 %0, %1, %2;" : "=r"(r) : "r"(a), "r"(b)); return r;
}
__device__ __forceinline__ uint32_t bmul2(uint32_t a, uint32_t b) {
  uint32_t r; asm("mul.rn.bf16x2 %0, %1, %2;" : "=r"(r) : "r"(a), "r"(b)); return r;
}
__device__ __forceinline__ uint32_t bfma2(uint32_t a, uint32_t b, uint32_t c) {
  uint32_t r; asm("fma.rn.bf16x2 %0, %1, %2, %3;" : "=r"(r) : "r"(a), "r"(b), "r"(c)); return r;
}
__device__ __forceinline__ float ex2(float x) {
  float y; asm("ex2.approx.ftz.f32 %0, %1;" : "=f"(y) : "f"(x)); return y;
}

struct DeqArgs {
  const int* qk; const int* qv;
  const __nv_bfloat16* ks; const __nv_bfloat16* kz; const __nv_bfloat16* vs; const __nv_bfloat16* vz;
  const __nv_bfloat16* q;
};
__device__ __forceinline__ uint32_t badd2(uint32_t a, uint32_t b) {
  uint32_t r; asm("add.rn.bf16x2 %0, %1, %2;" : "=r"(r) : "r"(a), "r"(b)); return r;
}
__device__ __forceinline__ uint32_t bmax2_nan(uint32_t a, uint32_t b) {
  uint32_t r; asm("max.NaN.bf16x2 %0, %1, %2;" : "=r"(r) : "r"(a), "r"(b)); return r;
}
__device__ __forceinline__ uint32_t bmaxabs2_nan(uint32_t a, uint32_t b) {
  uint32_t r; asm("max.NaN.xorsign.abs.bf16x2 %0, %1, %2;" : "=r"(r) : "r"(a), "r"(b)); return r;
}
constexpr uint32_t KSCALE_HI2 = 0x3e033e03u, KSCALE_LO2 = 0xb9d8b9d8u;

template <int NSTEP>
__device__ __forceinline__ void dequant_unit(const DeqArgs& a, int head, int isV, int tok0, int lane, uint32_t& kb2, uint32_t& vb2) {
  tok0 += lane >> 4;
  const int ch = lane & 15, blk = tok0 >> 7;
  const int row0 = head * SEQ + tok0;
  uint8_t* img = g_kv + (size_t)((isV * HKV + head) * NBLK + blk) * TILE_BYTES + (ch >> 3) * 16384;
  if (isV) {
    const int* src = a.qv + (size_t)row0 * DH + 32 * (ch >> 2) + 2 * (ch & 3);
    int2 v[NSTEP][4];
    uint32_t s1[NSTEP], z1[NSTEP];
#pragma unroll
    for (int it = 0; it < NSTEP; it++)
#pragma unroll
      for (int c = 0; c < 4; c++) v[it][c] = __ldg(reinterpret_cast<const int2*>(src + it * 2 * DH + 8 * c));
#pragma unroll
    for (int it = 0; it < NSTEP; it++) {
      s1[it] = __bfloat16_as_ushort(__ldg(a.vs + row0 + it * 2));
      z1[it] = __bfloat16_as_ushort(__ldg(a.vz + row0 + it * 2));
    }
#pragma unroll
    for (int it = 0; it < NSTEP; it++) {
      const int t = (row0 + it * 2) & (BLK - 1);
      const uint32_t s2 = s1[it] * 0x10001u, z2 = z1[it] * 0x10001u;
      uint32_t w[4];
#pragma unroll
      for (int c = 0; c < 4; c++) {
        const uint32_t x = pack_bf16(__int2float_rn(v[it][c].x), __int2float_rn(v[it][c].y));
        w[c] = bmul2(bsub2(x, z2), s2);
        vb2 = bmaxabs2_nan(vb2, w[c]);
      }
      *reinterpret_cast<uint4*>(img + t * 128 + (((ch & 7) ^ (t & 7)) << 4)) = make_uint4(w[0], w[1], w[2], w[3]);
    }
  } else {
    const int* src = a.qk + (size_t)row0 * DH + 8 * ch;
    int4 v[NSTEP][2];
#pragma unroll
    for (int it = 0; it < NSTEP; it++) {
      v[it][0] = __ldg(reinterpret_cast<const int4*>(src + it * 2 * DH));
      v[it][1] = __ldg(reinterpret_cast<const int4*>(src + it * 2 * DH + 4));
    }
    const int off = (head * NBLK + blk) * DH + 8 * ch;
    const uint4 s4 = __ldg(reinterpret_cast<const uint4*>(a.ks + off));
    const uint4 z4 = __ldg(reinterpret_cast<const uint4*>(a.kz + off));
    uint32_t n2[NSTEP];
#pragma unroll
    for (int it = 0; it < NSTEP; it++) {
      const int t = (row0 + it * 2) & (BLK - 1);
      const int x[8] = {v[it][0].x, v[it][0].y, v[it][0].z, v[it][0].w, v[it][1].x, v[it][1].y, v[it][1].z, v[it][1].w};
      const uint32_t sc[4] = {s4.x, s4.y, s4.z, s4.w}, zr[4] = {z4.x, z4.y, z4.z, z4.w};
      uint32_t w[4];
#pragma unroll
      for (int c = 0; c < 4; c++) {
        uint32_t y = pack_bf16(__int2float_rn(x[2 * c]), __int2float_rn(x[2 * c + 1]));
        y = bmul2(bsub2(y, zr[c]), sc[c]);
        w[c] = bfma2(y, KSCALE_HI2, bmul2(y, KSCALE_LO2));
        n2[it] = c == 0 ? bmul2(w[c], w[c]) : bfma2(w[c], w[c], n2[it]);
      }
      *reinterpret_cast<uint4*>(img + t * 128 + (((ch & 7) ^ (t & 7)) << 4)) = make_uint4(w[0], w[1], w[2], w[3]);
    }
#pragma unroll
    for (int it = 0; it < NSTEP; it += 2) {
      uint32_t n = badd2(__byte_perm(n2[it], n2[it + 1], 0x5410), __byte_perm(n2[it], n2[it + 1], 0x7632));
      n = badd2(n, __shfl_xor_sync(0xffffffffu, n, 1));
      n = badd2(n, __shfl_xor_sync(0xffffffffu, n, 2));
      n = badd2(n, __shfl_xor_sync(0xffffffffu, n, 4));
      n = badd2(n, __shfl_xor_sync(0xffffffffu, n, 8));
      kb2 = bmax2_nan(kb2, n);
    }
  }
}
__device__ __forceinline__ uint32_t warp_max_bits(uint32_t m2) {
  return __reduce_max_sync(0xffffffffu, max((m2 << 16) & 0x7fff0000u, m2 & 0x7fff0000u));
}
__device__ __forceinline__ void publish(int head, uint32_t rows, uint32_t kbest, uint32_t vbest) {
  asm volatile("red.relaxed.gpu.global.max.u32 [%0], %1;" ::"l"(g_kn2 + head), "r"(kbest) : "memory");
  asm volatile("red.relaxed.gpu.global.max.u32 [%0], %1;" ::"l"(g_vmax + head), "r"(vbest) : "memory");
  asm volatile("red.release.gpu.global.add.u32 [%0], %1;" ::"l"(g_ready + head), "r"(rows) : "memory");
}
__device__ __forceinline__ uint32_t ld_acquire(const uint32_t* p) {
  uint32_t v; asm volatile("ld.acquire.gpu.global.u32 %0, [%1];" : "=r"(v) : "l"(p) : "memory"); return v;
}
__device__ __forceinline__ uint32_t ld_relaxed(const uint32_t* p) {
  uint32_t v; asm volatile("ld.relaxed.gpu.global.u32 %0, [%1];" : "=r"(v) : "l"(p) : "memory"); return v;
}

__device__ __forceinline__ void mbar_init(uint32_t bar, uint32_t count) {
  asm volatile("mbarrier.init.shared::cta.b64 [%0], %1;" ::"r"(bar), "r"(count) : "memory");
}
__device__ __forceinline__ void mbar_expect_tx(uint32_t bar, uint32_t bytes) {
  asm volatile("mbarrier.arrive.expect_tx.shared::cta.b64 _, [%0], %1;" ::"r"(bar), "r"(bytes) : "memory");
}
__device__ __forceinline__ void mbar_arrive(uint32_t bar) {
  asm volatile("mbarrier.arrive.shared::cta.b64 _, [%0];" ::"r"(bar) : "memory");
}
__device__ __forceinline__ void mbar_wait(uint32_t bar, uint32_t parity) {
  asm volatile(
      "{\n"
      ".reg .pred p;\n"
      "WAIT_LOOP:\n"
      "mbarrier.try_wait.parity.shared::cta.b64 p, [%0], %1;\n"
      "@p bra.uni WAIT_DONE;\n"
      "bra.uni WAIT_LOOP;\n"
      "WAIT_DONE:\n"
      "}\n" ::"r"(bar), "r"(parity) : "memory");
}
__device__ __forceinline__ void bulk_load(uint32_t dst, const void* src, uint32_t bytes, uint32_t bar) {
  asm volatile("cp.async.bulk.shared::cluster.global.mbarrier::complete_tx::bytes [%0], [%1], %2, [%3];"
               ::"r"(dst), "l"(src), "r"(bytes), "r"(bar) : "memory");
}
__device__ __forceinline__ void wg_fence() { asm volatile("wgmma.fence.sync.aligned;" ::: "memory"); }
__device__ __forceinline__ void wg_commit() { asm volatile("wgmma.commit_group.sync.aligned;" ::: "memory"); }
template <int N> __device__ __forceinline__ void wg_wait() { asm volatile("wgmma.wait_group.sync.aligned %0;" ::"n"(N) : "memory"); }
__device__ __forceinline__ void bar_sync(int id) { asm volatile("bar.sync %0, 256;" ::"r"(id) : "memory"); }
__device__ __forceinline__ void bar_arrive(int id) { asm volatile("bar.arrive %0, 256;" ::"r"(id) : "memory"); }

#define A8(d, o) "+f"(d[o + 0]), "+f"(d[o + 1]), "+f"(d[o + 2]), "+f"(d[o + 3]), "+f"(d[o + 4]), "+f"(d[o + 5]), "+f"(d[o + 6]), "+f"(d[o + 7])
#define ACC64(d) A8(d, 0), A8(d, 8), A8(d, 16), A8(d, 24), A8(d, 32), A8(d, 40), A8(d, 48), A8(d, 56)
#define REGS64                                                                                \
  "{%0, %1, %2, %3, %4, %5, %6, %7, %8, %9, %10, %11, %12, %13, %14, %15, "                   \
  "%16, %17, %18, %19, %20, %21, %22, %23, %24, %25, %26, %27, %28, %29, %30, %31, "          \
  "%32, %33, %34, %35, %36, %37, %38, %39, %40, %41, %42, %43, %44, %45, %46, %47, "          \
  "%48, %49, %50, %51, %52, %53, %54, %55, %56, %57, %58, %59, %60, %61, %62, %63}"

template <int TB>
__device__ __forceinline__ void mma_rs(float (&d)[64], uint32_t a0, uint32_t a1, uint32_t a2, uint32_t a3,
                                       uint64_t desc, int scale_d) {
  asm volatile(
      "{\n.reg .pred p;\nsetp.ne.b32 p, %69, 0;\n"
      "wgmma.mma_async.sync.aligned.m64n128k16.f32.bf16.bf16 " REGS64
      ", {%64, %65, %66, %67}, %68, p, 1, 1, %70;\n}\n"
      : ACC64(d)
      : "r"(a0), "r"(a1), "r"(a2), "r"(a3), "l"(desc), "r"(scale_d), "n"(TB));
}
__device__ __forceinline__ void fence_regs(float (&d)[64]) {
#pragma unroll
  for (int i = 0; i < 64; i++) asm volatile("" : "+f"(d[i])::"memory");
}
__device__ __forceinline__ void fence_regs_u(uint32_t (&d)[32]) {
#pragma unroll
  for (int i = 0; i < 32; i++) asm volatile("" : "+r"(d[i])::"memory");
}

__device__ __forceinline__ uint64_t make_desc(uint32_t addr, uint32_t lbo_bytes) {
  return (uint64_t)((addr & 0x3FFFF) >> 4) | ((uint64_t)(lbo_bytes >> 4) << 16) | ((uint64_t)(1024 >> 4) << 32) |
         ((uint64_t)1 << 62);
}

__device__ __forceinline__ void issue_qk(float (&S)[64], const uint32_t (&Q)[32], uint32_t kaddr) {
  const uint64_t d0 = make_desc(kaddr, 16);
#pragma unroll
  for (int kk = 0; kk < 8; kk++) {
    const uint64_t off = (uint64_t)(((kk >> 2) * 16384 + (kk & 3) * 32) >> 4);
    mma_rs<0>(S, Q[kk * 4 + 0], Q[kk * 4 + 1], Q[kk * 4 + 2], Q[kk * 4 + 3], d0 + off, kk != 0);
  }
}
__device__ __forceinline__ void issue_pv(float (&O)[64], const uint32_t (&P)[32], uint32_t vaddr, int acc) {
  const uint64_t d0 = make_desc(vaddr, 16384);
#pragma unroll
  for (int kk = 0; kk < 8; kk++)
    mma_rs<1>(O, P[kk * 4 + 0], P[kk * 4 + 1], P[kk * 4 + 2], P[kk * 4 + 3], d0 + (uint64_t)((kk * 2048) >> 4),
              kk == 0 ? acc : 1);
}

__device__ __forceinline__ void tma_load_2d(uint32_t dst, const CUtensorMap* tm, int c0, int c1, uint32_t bar) {
  asm volatile("cp.async.bulk.tensor.2d.shared::cluster.global.mbarrier::complete_tx::bytes [%0], [%1, {%3, %4}], [%2];"
               ::"r"(dst), "l"(tm), "r"(bar), "r"(c0), "r"(c1) : "memory");
}
__device__ __forceinline__ void load_q(uint32_t (&Q)[32], uint32_t qaddr) {
#pragma unroll
  for (int kk = 0; kk < 8; kk++)
    asm volatile("ldmatrix.sync.aligned.m8n8.x4.shared.b16 {%0, %1, %2, %3}, [%4];"
                 : "=r"(Q[kk * 4 + 0]), "=r"(Q[kk * 4 + 1]), "=r"(Q[kk * 4 + 2]), "=r"(Q[kk * 4 + 3])
                 : "r"((qaddr ^ ((kk & 3) << 5)) + (kk >> 2) * 16384) : "memory");
}

__device__ __forceinline__ float q_norm(const uint32_t (&Q)[32]) {
  uint32_t a0 = 0, a1 = 0, b0 = 0, b1 = 0;
#pragma unroll
  for (int i = 0; i < 8; i++) {
    a0 = bfma2(Q[4 * i + 0], Q[4 * i + 0], a0);
    a1 = bfma2(Q[4 * i + 2], Q[4 * i + 2], a1);
    b0 = bfma2(Q[4 * i + 1], Q[4 * i + 1], b0);
    b1 = bfma2(Q[4 * i + 3], Q[4 * i + 3], b1);
  }
  float n0 = (bf_lo(a0) + bf_hi(a0)) + (bf_lo(a1) + bf_hi(a1));
  float n1 = (bf_lo(b0) + bf_hi(b0)) + (bf_lo(b1) + bf_hi(b1));
  n0 += __shfl_xor_sync(0xffffffffu, n0, 1);
  n1 += __shfl_xor_sync(0xffffffffu, n1, 1);
  n0 += __shfl_xor_sync(0xffffffffu, n0, 2);
  n1 += __shfl_xor_sync(0xffffffffu, n1, 2);
  const uint32_t m = max(__float_as_uint(n0) & 0x7fffffffu, __float_as_uint(n1) & 0x7fffffffu);
  const float n = __uint_as_float(__reduce_max_sync(0xffffffffu, m));
  return fmaf(n, 1.06f, 1e-30f);
}
__device__ __forceinline__ float lds_f32(uint32_t addr) {
  float v; asm volatile("ld.shared.f32 %0, [%1];" : "=f"(v) : "r"(addr) : "memory"); return v;
}

__global__ void __launch_bounds__(384, 1) attn_kernel(const __grid_constant__ CUtensorMap tmap_q, const __grid_constant__ DeqArgs deq,
                                                      __nv_bfloat16* __restrict__ out, int first_helper) {
  extern __shared__ uint8_t smem_raw[];
  const uint32_t smem_base = (smem_u32(smem_raw) + 1023u) & ~1023u;
  const uint32_t q_smem = smem_base + NSLOT * TILE_BYTES;
  const uint32_t bar_full = q_smem + TILE_BYTES;
  const uint32_t bar_empty = bar_full + 8 * NSLOT;
  const uint32_t bar_qfull = bar_empty + 8 * NSLOT;
  const uint32_t bar_qempty = bar_qfull + 8;
  const uint32_t bar_meta = bar_qempty + 8;
  const uint32_t meta_smem = bar_meta + 8;
  const uint32_t red_smem = bar_full + 512;
  const int tid = threadIdx.x;
  const int warp = __shfl_sync(0xffffffffu, tid >> 5, 0);
  const int lane = tid & 31;
  TR3C(0);

  if (warp < 8) {
    uint32_t kb2 = 0, vb2 = 0, rows = 0;
    for (int u = (int)blockIdx.x * 8 + warp; u < 2 * SEQ / 4; u += (int)gridDim.x * 8) {
      dequant_unit<2>(deq, 0, u >= SEQ / 4, (u & (SEQ / 4 - 1)) * 4, lane, kb2, vb2);
      rows += 4;
    }
    TR3C(2);
    const uint32_t kbest = warp_max_bits(kb2), vbest = warp_max_bits(vb2);
    if (lane == 0) asm volatile("st.shared.v4.u32 [%0], {%1, %2, %3, %3};" ::"r"(red_smem + 16 * warp), "r"(kbest), "r"(vbest), "r"(rows) : "memory");
  } else if (tid == 256) {
    asm volatile("prefetch.tensormap [%0];" ::"l"(&tmap_q) : "memory");
#pragma unroll
    for (int s = 0; s < NSLOT; s++) {
      mbar_init(bar_full + 8 * s, 1);
      mbar_init(bar_empty + 8 * s, 8);
    }
    mbar_init(bar_qfull, 1);
    mbar_init(bar_qempty, 8);
    mbar_init(bar_meta, 1);
    asm volatile("fence.mbarrier_init.release.cluster;" ::: "memory");
  }
  __syncthreads();
  TR3C(1);
  if (warp == 8) {
    uint32_t k = 0, v = 0, n = 0;
    if (lane < 8) {
      asm volatile("ld.shared.v2.u32 {%0, %1}, [%2];" : "=r"(k), "=r"(v) : "r"(red_smem + 16 * lane) : "memory");
      asm volatile("ld.shared.u32 %0, [%1];" : "=r"(n) : "r"(red_smem + 16 * lane + 8) : "memory");
    }
    k = __reduce_max_sync(0xffffffffu, k);
    v = __reduce_max_sync(0xffffffffu, v);
    n = __reduce_add_sync(0xffffffffu, n);
    if (lane == 0 && n) publish(0, n, k, v);
    __syncwarp();
  }

  if ((int)blockIdx.x >= first_helper) {
    const int nh = (int)gridDim.x - first_helper, hb = (int)blockIdx.x - first_helper;
    constexpr int UPH = 2 * SEQ / 16;
    int buf = 1;
    __syncthreads();
#pragma unroll 1
    for (int u0 = 0; u0 < (HKV - 1) * UPH; u0 += 12 * nh, buf ^= 1) {
      const int u = u0 + warp * nh + hb;
      uint32_t kb2 = 0, vb2 = 0, rows = 0;
      const int head = 1 + u / UPH;
      if (u < (HKV - 1) * UPH) {
        const int w = u % UPH;
        dequant_unit<8>(deq, head, w >= UPH / 2, (w & (UPH / 2 - 1)) * 16, lane, kb2, vb2);
        rows = 16;
      }
      const uint32_t kbest = warp_max_bits(kb2), vbest = warp_max_bits(vb2);
      const uint32_t red = red_smem + buf * 192;
      if (lane == 0) asm volatile("st.shared.v4.u32 [%0], {%1, %2, %3, %4};" ::"r"(red + 16 * warp), "r"(kbest), "r"(vbest), "r"(rows), "r"(head) : "memory");
      __syncthreads();
      if (warp == 9 + buf) {
        uint32_t k = 0, v = 0, n = 0, hd = 0;
        if (lane < 12) asm volatile("ld.shared.v4.u32 {%0, %1, %2, %3}, [%4];" : "=r"(k), "=r"(v), "=r"(n), "=r"(hd) : "r"(red + 16 * lane) : "memory");
        for (int h = 1; h < HKV; h++) {
          const bool m = (int)hd == h;
          const uint32_t hk = __reduce_max_sync(0xffffffffu, m ? k : 0u), hv = __reduce_max_sync(0xffffffffu, m ? v : 0u);
          const uint32_t hn = __reduce_add_sync(0xffffffffu, m ? n : 0u);
          if (lane == 0 && hn) publish(h, hn, hk, hv);
        }
        __syncwarp();
      }
    }
    __syncthreads();
  }

  if (warp >= 8) {
    asm volatile("setmaxnreg.dec.sync.aligned.u32 56;");
    if (warp == 8) {
      if (lane == 0) {
        const int ntile = (NTILES - (int)blockIdx.x + (int)gridDim.x - 1) / (int)gridDim.x;
        const int total = ntile * NBLK;
        auto load_qtile = [&](int r) {
          const int row = ((int)blockIdx.x + r * (int)gridDim.x) * TILE_M;
          mbar_expect_tx(bar_qfull, TILE_BYTES);
          tma_load_2d(q_smem, &tmap_q, 0, row, bar_qfull);
          tma_load_2d(q_smem + 16384, &tmap_q, 64, row, bar_qfull);
        };
        auto wait_head = [&](int r) {
          const uint32_t* flag = g_ready + ((int)blockIdx.x + r * (int)gridDim.x) / TILES_PER_KVH;
          while (ld_acquire(flag) < 2 * SEQ) {}
          asm volatile("fence.proxy.async;" ::: "memory");
        };
        auto post_meta = [&](int r) {
          const int h = ((int)blockIdx.x + r * (int)gridDim.x) / TILES_PER_KVH;
          const uint32_t k = ld_relaxed(g_kn2 + h), v = ld_relaxed(g_vmax + h);
          float kn2 = fmaf(__uint_as_float(k), 1.03f, 1e-30f);
          if (v < VMAX_LO || v > VMAX_HI) kn2 = INFINITY;
          asm volatile("st.shared.f32 [%0], %1;" ::"r"(meta_smem + 4 * (r & 1)), "f"(kn2) : "memory");
          mbar_arrive(bar_meta);
        };
        load_qtile(0);
        TR3(2, 2);
        wait_head(0);
        TR3(2, 3);
        int slot = 0;
        uint32_t phase = 1;
        const uint8_t* kbase = g_kv;
        const uint8_t* vbase = g_kv + (size_t)HKV * NBLK * TILE_BYTES;
        auto load = [&](const uint8_t* base, int it) {
          const int u = (int)blockIdx.x + (it >> 4) * (int)gridDim.x;
          const uint8_t* src = base + (size_t)((u / TILES_PER_KVH) * NBLK + (it & 15)) * TILE_BYTES;
          mbar_wait(bar_empty + 8 * slot, phase);
          mbar_expect_tx(bar_full + 8 * slot, TILE_BYTES);
          bulk_load(smem_base + slot * TILE_BYTES, src, TILE_BYTES, bar_full + 8 * slot);
          if (++slot == NSLOT) { slot = 0; phase ^= 1; }
        };
        load(kbase, 0);
        TR3(2, 4);
        post_meta(0);
        for (int it = 0; it < total - 1; it++) {
          if ((it & 15) == 10 && (it >> 4) + 1 < ntile) {
            wait_head((it >> 4) + 1);
            post_meta((it >> 4) + 1);
            mbar_wait(bar_qempty, (it >> 4) & 1);
            load_qtile((it >> 4) + 1);
          }
          load(kbase, it + 1);
          load(vbase, it);
        }
        load(vbase, total - 1);
      }
    }
  } else {
    asm volatile("setmaxnreg.inc.sync.aligned.u32 224;");
    TR3C(5);
    const int ntile = (NTILES - (int)blockIdx.x + (int)gridDim.x - 1) / (int)gridDim.x;
    const int total = ntile * NBLK;
    const int wg = warp >> 2;
    const int g = lane >> 2, c = lane & 3;
    const int row0 = wg * 64 + (warp & 3) * 16;
    __nv_bfloat16* optr = out + ((size_t)blockIdx.x * TILE_M + row0 + g) * DH + c * 8;
    const uint32_t q_lane = q_smem + (row0 + (lane & 15)) * 128 + (((lane >> 4) ^ (lane & 7)) << 4);

    float S[64], O[64];
    uint32_t P[32], Q[32];
    float l0 = 0.f, l1 = 0.f, m0 = -INFINITY, m1 = -INFINITY;
    float lf0 = 0.f, lf1 = 0.f;
    int slot = 0;
    uint32_t phase = 0;
    auto advance = [&]() { if (++slot == NSLOT) { slot = 0; phase ^= 1; } };

    TRACE_PT(0);
    mbar_wait(bar_qfull, 0);
    TR3C(6);
    load_q(Q, q_lane);
    __syncwarp();
    if (lane == 0) mbar_arrive(bar_qempty);
    const float qn_first = q_norm(Q);
    bool fast;

    float al0 = 1.f, al1 = 1.f;
    bool resc = false;
    auto softmax = [&]() {
      if (fast) {
#pragma unroll
        for (int i = 0; i < 64; i += 4) {
          S[i + 0] = ex2(S[i + 0]); S[i + 1] = ex2(S[i + 1]);
          S[i + 2] = ex2(S[i + 2]); S[i + 3] = ex2(S[i + 3]);
          l0 += S[i + 0]; l1 += S[i + 2];
          l0 += S[i + 1]; l1 += S[i + 3];
        }
      } else {
        float x0 = fmaxf(S[0], S[1]), x1 = fmaxf(S[2], S[3]);
#pragma unroll
        for (int i = 4; i < 64; i += 4) {
          x0 = fmaxf(x0, fmaxf(S[i + 0], S[i + 1]));
          x1 = fmaxf(x1, fmaxf(S[i + 2], S[i + 3]));
        }
        x0 = fmaxf(x0, __shfl_xor_sync(0xffffffffu, x0, 1));
        x1 = fmaxf(x1, __shfl_xor_sync(0xffffffffu, x1, 1));
        x0 = fmaxf(x0, __shfl_xor_sync(0xffffffffu, x0, 2));
        x1 = fmaxf(x1, __shfl_xor_sync(0xffffffffu, x1, 2));
        const bool need = (x0 > m0 + 8.f) || (x1 > m1 + 8.f);
        resc = __any_sync(0xffffffffu, need);
        if (resc) {
          const float n0 = fmaxf(m0, x0), n1 = fmaxf(m1, x1);
          al0 = (n0 == -INFINITY) ? 1.f : ex2(m0 - n0);
          al1 = (n1 == -INFINITY) ? 1.f : ex2(m1 - n1);
          m0 = n0; m1 = n1;
          l0 *= al0; l1 *= al1;
        }
        const float s0 = (m0 == -INFINITY) ? 0.f : m0, s1 = (m1 == -INFINITY) ? 0.f : m1;
#pragma unroll
        for (int i = 0; i < 64; i += 4) {
          S[i + 0] = ex2(S[i + 0] - s0); S[i + 1] = ex2(S[i + 1] - s0);
          S[i + 2] = ex2(S[i + 2] - s1); S[i + 3] = ex2(S[i + 3] - s1);
          l0 += S[i + 0]; l1 += S[i + 2];
          l0 += S[i + 1]; l1 += S[i + 3];
        }
      }
    };
    auto pack_p = [&]() {
#pragma unroll
      for (int i = 0; i < 32; i++) P[i] = pack_bf16(S[2 * i], S[2 * i + 1]);
    };
    auto finish_l = [&](float& e0, float& e1) {
      e0 += __shfl_xor_sync(0xffffffffu, e0, 1);
      e1 += __shfl_xor_sync(0xffffffffu, e1, 1);
      e0 += __shfl_xor_sync(0xffffffffu, e0, 2);
      e1 += __shfl_xor_sync(0xffffffffu, e1, 2);
      asm("rcp.approx.ftz.f32 %0, %0;" : "+f"(e0));
      asm("rcp.approx.ftz.f32 %0, %0;" : "+f"(e1));
    };
    auto epilogue = [&](float r0, float r1) {
#pragma unroll
      for (int J = 0; J < 4; J++) {
        float* o = &O[16 * J];
        const uint32_t a0 = pack_bf16(o[0] * r0, o[1] * r0), a1 = pack_bf16(o[4] * r0, o[5] * r0);
        const uint32_t b0 = pack_bf16(o[2] * r1, o[3] * r1), b1 = pack_bf16(o[6] * r1, o[7] * r1);
        const uint32_t a2 = pack_bf16(o[8] * r0, o[9] * r0), a3 = pack_bf16(o[12] * r0, o[13] * r0);
        const uint32_t b2 = pack_bf16(o[10] * r1, o[11] * r1), b3 = pack_bf16(o[14] * r1, o[15] * r1);
        o[0] = __uint_as_float(a0); o[1] = __uint_as_float(a1); o[2] = __uint_as_float(a2); o[3] = __uint_as_float(a3);
        o[4] = __uint_as_float(b0); o[5] = __uint_as_float(b1); o[6] = __uint_as_float(b2); o[7] = __uint_as_float(b3);
        asm volatile("st.global.v4.f32 [%0], {%1, %2, %3, %4};" ::"l"(optr + J * 32), "f"(o[0]), "f"(o[1]), "f"(o[2]), "f"(o[3]) : "memory");
        asm volatile("st.global.v4.f32 [%0], {%1, %2, %3, %4};" ::"l"(optr + 8 * DH + J * 32), "f"(o[4]), "f"(o[5]), "f"(o[6]), "f"(o[7]) : "memory");
      }
    };

    if (wg == 1) bar_arrive(1);
    TR3C(7);
    mbar_wait(bar_full + 8 * slot, phase);
    TR3C(8);
    wg_fence();
    issue_qk(S, Q, smem_base + slot * TILE_BYTES);
    wg_commit();
    mbar_wait(bar_meta, 0);
    fast = qn_first * lds_f32(meta_smem) <= FAST_BOUND2;
    TR3C(9);
    wg_wait<0>();
    fence_regs(S);
    TR3C(10);
    if (lane == 0) mbar_arrive(bar_empty + 8 * slot);
    advance();
    softmax();
    TR3C(11);
    pack_p();
    TR3C(12);

    for (int it = 0; it < total - 1; it++) {
      const int j = it & 15;
      const int kslot = slot;
      const uint32_t kphase = phase;
      advance();
      const int vslot = slot;
      const uint32_t vphase = phase;
      advance();

      TRACE_PT(it + 1);
      TR2(0);
      bar_sync(1 + wg);
      TR2(1);
      mbar_wait(bar_full + 8 * kslot, kphase);
      mbar_wait(bar_full + 8 * vslot, vphase);
      wg_fence();
      issue_qk(S, Q, smem_base + kslot * TILE_BYTES);
      wg_commit();
      TR2(2);
      if (j == 15) {
        mbar_wait(bar_meta, ((it >> 4) + 1) & 1);
        fast = q_norm(Q) * lds_f32(meta_smem + 4 * (((it >> 4) + 1) & 1)) <= FAST_BOUND2;
        lf0 = l0; lf1 = l1;
        finish_l(lf0, lf1);
        l0 = 0.f; l1 = 0.f; m0 = -INFINITY; m1 = -INFINITY;
      } else if (j == 0 && it != 0) {
        epilogue(lf0, lf1);
        optr += (size_t)gridDim.x * TILE_M * DH;
      }
      wg_fence();
      issue_pv(O, P, smem_base + vslot * TILE_BYTES, j != 0);
      wg_commit();
      TR2(3);
      bar_arrive(2 - wg);

      wg_wait<1>();
      fence_regs(S);
      TR2(4);
      if (lane == 0) mbar_arrive(bar_empty + 8 * kslot);
      if (j == 14 && it + 2 < total) {
        mbar_wait(bar_qfull, ((it >> 4) + 1) & 1);
        load_q(Q, q_lane);
        __syncwarp();
        if (lane == 0) mbar_arrive(bar_qempty);
      }
      resc = false;
      softmax();
      TR2(5);
      wg_wait<0>();
      fence_regs(O);
      fence_regs_u(P);
      TR2(6);
      if (lane == 0) mbar_arrive(bar_empty + 8 * vslot);
      if (resc && j != 15) {
#pragma unroll
        for (int i = 0; i < 64; i += 4) {
          O[i + 0] *= al0; O[i + 1] *= al0; O[i + 2] *= al1; O[i + 3] *= al1;
        }
      }
      pack_p();
      TR2(7);
    }
    bar_sync(1 + wg);
    mbar_wait(bar_full + 8 * slot, phase);
    wg_fence();
    issue_pv(O, P, smem_base + slot * TILE_BYTES, 1);
    wg_commit();
    if (wg == 0) bar_arrive(2);
    wg_wait<0>();
    fence_regs(O);
    finish_l(l0, l1);
    epilogue(l0, l1);
    if (tid == 0) {
      __threadfence();
      if (atomicAdd(&g_done, 1u) == gridDim.x - 1) {
#pragma unroll
        for (int h = 0; h < HKV; h++) { g_ready[h] = 0; g_kn2[h] = 0; g_vmax[h] = 0; }
        g_done = 0;
      }
    }
    TRACE_PT(65);
  }
}

}

extern "C" void kernel_launch(void* const* d_in, const int* in_sizes, int n_in, void* d_out, int out_size) {
  const __nv_bfloat16* q = (const __nv_bfloat16*)d_in[0];
  const int* qk = (const int*)d_in[1];
  const int* qv = (const int*)d_in[2];
  const __nv_bfloat16* ks = (const __nv_bfloat16*)d_in[3];
  const __nv_bfloat16* kz = (const __nv_bfloat16*)d_in[4];
  const __nv_bfloat16* vs = (const __nv_bfloat16*)d_in[5];
  const __nv_bfloat16* vz = (const __nv_bfloat16*)d_in[6];
  __nv_bfloat16* out = (__nv_bfloat16*)d_out;

  typedef CUresult (*EncodeFn)(CUtensorMap*, CUtensorMapDataType, cuuint32_t, void*, const cuuint64_t*, const cuuint64_t*,
                               const cuuint32_t*, const cuuint32_t*, CUtensorMapInterleave, CUtensorMapSwizzle,
                               CUtensorMapL2promotion, CUtensorMapFloatOOBfill);
  static int num_sms = 0;
  static EncodeFn encode = nullptr;
  if (num_sms == 0) {
    int dev = 0;
    cudaGetDevice(&dev);
    cudaDeviceGetAttribute(&num_sms, cudaDevAttrMultiProcessorCount, dev);
    cudaFuncSetAttribute(attn_kernel, cudaFuncAttributeMaxDynamicSharedMemorySize, SMEM_BYTES);
    void* fn = nullptr;
    cudaDriverEntryPointQueryResult qres;
    cudaGetDriverEntryPoint("cuTensorMapEncodeTiled", &fn, cudaEnableDefault, &qres);
    encode = (EncodeFn)fn;
  }
  CUtensorMap tmap_q;
  {
    const cuuint64_t gdim[2] = {(cuuint64_t)DH, (cuuint64_t)ROWS};
    const cuuint64_t gstride[1] = {(cuuint64_t)DH * 2};
    const cuuint32_t box[2] = {64, (cuuint32_t)TILE_M};
    const cuuint32_t estride[2] = {1, 1};
    encode(&tmap_q, CU_TENSOR_MAP_DATA_TYPE_BFLOAT16, 2, (void*)q, gdim, gstride, box, estride, CU_TENSOR_MAP_INTERLEAVE_NONE,
           CU_TENSOR_MAP_SWIZZLE_128B, CU_TENSOR_MAP_L2_PROMOTION_L2_256B, CU_TENSOR_MAP_FLOAT_OOB_FILL_NONE);
  }
  DeqArgs deq{qk, qv, ks, kz, vs, vz, q};
  int grid = num_sms < NTILES ? num_sms : NTILES;
  int first_helper = NTILES % grid;
  if (grid - first_helper < 8) first_helper = 0;
  attn_kernel<<<grid, 384, SMEM_BYTES>>>(tmap_q, deq, out, first_helper);
}
```

```cpp
#include <cuda_runtime.h>
#include <cuda.h>
#include <cuda_bf16.h>
#include <stdint.h>

namespace {

constexpr int HQ = 32, HKV = 4, SEQ = 2048, DH = 128;
constexpr int BLK = 128;
constexpr int NBLK = SEQ / BLK;
constexpr int TILE_BYTES = BLK * DH * 2;
constexpr int ROWS = HQ * SEQ;
constexpr int TILE_M = 128;
constexpr int NTILES = ROWS / TILE_M;
constexpr int TILES_PER_KVH = NTILES / HKV;
constexpr int NSLOT = 6;
constexpr int SMEM_BYTES = (NSLOT + 1) * TILE_BYTES + 1024 + 256 + 1024;

constexpr float FAST_BOUND2 = 2500.0f;
constexpr uint32_t VMAX_LO = 0x2B800000u;
constexpr uint32_t VMAX_HI = 0x5D800000u;

__device__ __align__(1024) uint8_t g_kv[2 * HKV * NBLK * TILE_BYTES];
__device__ uint32_t g_ready[HKV];
__device__ uint32_t g_kn2[HKV];
__device__ uint32_t g_vmax[HKV];
__device__ uint32_t g_done;

#define TRACE_PT(idx)
#define TR2(k)
#define TR3(role, k)
#define TR3C(k)
__device__ __forceinline__ uint32_t smem_u32(const void* p) { return (uint32_t)__cvta_generic_to_shared(p); }

__device__ __forceinline__ uint32_t pack_bf16(float lo, float hi) {
  uint32_t r;
  asm("cvt.rn.bf16x2.f32 %0, %1, %2;" : "=r"(r) : "f"(hi), "f"(lo));
  return r;
}
__device__ __forceinline__ float bf_lo(uint32_t v) { return __uint_as_float(v << 16); }
__device__ __forceinline__ float bf_hi(uint32_t v) { return __uint_as_float(v & 0xffff0000u); }
__device__ __forceinline__ uint32_t bsub2(uint32_t a, uint32_t b) {
  uint32_t r; asm("sub.rn.bf16x2 %0, %1, %2;" : "=r"(r) : "r"(a), "r"(b)); return r;
}
__device__ __forceinline__ uint32_t bmul2(uint32_t a, uint32_t b) {
  uint32_t r; asm("mul.rn.bf16x2 %0, %1, %2;" : "=r"(r) : "r"(a), "r"(b)); return r;
}
__device__ __forceinline__ uint32_t bfma2(uint32_t a, uint32_t b, uint32_t c) {
  uint32_t r; asm("fma.rn.bf16x2 %0, %1, %2, %3;" : "=r"(r) : "r"(a), "r"(b), "r"(c)); return r;
}
__device__ __forceinline__ float ex2(float x) {
  float y; asm("ex2.approx.ftz.f32 %0, %1;" : "=f"(y) : "f"(x)); return y;
}

struct DeqArgs {
  const int* qk; const int* qv;
  const __nv_bfloat16* ks; const __nv_bfloat16* kz; const __nv_bfloat16* vs; const __nv_bfloat16* vz;
  const __nv_bfloat16* q;
};
__device__ __forceinline__ uint32_t badd2(uint32_t a, uint32_t b) {
  uint32_t r; asm("add.rn.bf16x2 %0, %1, %2;" : "=r"(r) : "r"(a), "r"(b)); return r;
}
__device__ __forceinline__ uint32_t bmax2_nan(uint32_t a, uint32_t b) {
  uint32_t r; asm("max.NaN.bf16x2 %0, %1, %2;" : "=r"(r) : "r"(a), "r"(b)); return r;
}
__device__ __forceinline__ uint32_t bmaxabs2_nan(uint32_t a, uint32_t b) {
  uint32_t r; asm("max.NaN.xorsign.abs.bf16x2 %0, %1, %2;" : "=r"(r) : "r"(a), "r"(b)); return r;
}
constexpr uint32_t KSCALE_HI2 = 0x3e033e03u, KSCALE_LO2 = 0xb9d8b9d8u;

template <int NSTEP>
__device__ __forceinline__ void dequant_unit(const DeqArgs& a, int head, int isV, int tok0, int lane, uint32_t& kb2, uint32_t& vb2) {
  tok0 += lane >> 4;
  const int ch = lane & 15, blk = tok0 >> 7;
  const int row0 = head * SEQ + tok0;
  uint8_t* img = g_kv + (size_t)((isV * HKV + head) * NBLK + blk) * TILE_BYTES + (ch >> 3) * 16384;
  if (isV) {
    const int* src = a.qv + (size_t)row0 * DH + 32 * (ch >> 2) + 2 * (ch & 3);
    int2 v[NSTEP][4];
    uint32_t s1[NSTEP], z1[NSTEP];
#pragma unroll
    for (int it = 0; it < NSTEP; it++)
#pragma unroll
      for (int c = 0; c < 4; c++) v[it][c] = __ldg(reinterpret_cast<const int2*>(src + it * 2 * DH + 8 * c));
#pragma unroll
    for (int it = 0; it < NSTEP; it++) {
      s1[it] = __bfloat16_as_ushort(__ldg(a.vs + row0 + it * 2));
      z1[it] = __bfloat16_as_ushort(__ldg(a.vz + row0 + it * 2));
    }
#pragma unroll
    for (int it = 0; it < NSTEP; it++) {
      const int t = (row0 + it * 2) & (BLK - 1);
      const uint32_t s2 = s1[it] * 0x10001u, z2 = z1[it] * 0x10001u;
      uint32_t w[4];
#pragma unroll
      for (int c = 0; c < 4; c++) {
        const uint32_t x = pack_bf16(__int2float_rn(v[it][c].x), __int2float_rn(v[it][c].y));
        w[c] = bmul2(bsub2(x, z2), s2);
        vb2 = bmaxabs2_nan(vb2, w[c]);
      }
      *reinterpret_cast<uint4*>(img + t * 128 + (((ch & 7) ^ (t & 7)) << 4)) = make_uint4(w[0], w[1], w[2], w[3]);
    }
  } else {
    const int* src = a.qk + (size_t)row0 * DH + 8 * ch;
    int4 v[NSTEP][2];
#pragma unroll
    for (int it = 0; it < NSTEP; it++) {
      v[it][0] = __ldg(reinterpret_cast<const int4*>(src + it * 2 * DH));
      v[it][1] = __ldg(reinterpret_cast<const int4*>(src + it * 2 * DH + 4));
    }
    const int off = (head * NBLK + blk) * DH + 8 * ch;
    const uint4 s4 = __ldg(reinterpret_cast<const uint4*>(a.ks + off));
    const uint4 z4 = __ldg(reinterpret_cast<const uint4*>(a.kz + off));
    uint32_t n2[NSTEP];
#pragma unroll
    for (int it = 0; it < NSTEP; it++) {
      const int t = (row0 + it * 2) & (BLK - 1);
      const int x[8] = {v[it][0].x, v[it][0].y, v[it][0].z, v[it][0].w, v[it][1].x, v[it][1].y, v[it][1].z, v[it][1].w};
      const uint32_t sc[4] = {s4.x, s4.y, s4.z, s4.w}, zr[4] = {z4.x, z4.y, z4.z, z4.w};
      uint32_t w[4];
#pragma unroll
      for (int c = 0; c < 4; c++) {
        uint32_t y = pack_bf16(__int2float_rn(x[2 * c]), __int2float_rn(x[2 * c + 1]));
        y = bmul2(bsub2(y, zr[c]), sc[c]);
        w[c] = bfma2(y, KSCALE_HI2, bmul2(y, KSCALE_LO2));
        n2[it] = c == 0 ? bmul2(w[c], w[c]) : bfma2(w[c], w[c], n2[it]);
      }
      *reinterpret_cast<uint4*>(img + t * 128 + (((ch & 7) ^ (t & 7)) << 4)) = make_uint4(w[0], w[1], w[2], w[3]);
    }
#pragma unroll
    for (int it = 0; it < NSTEP; it += 2) {
      uint32_t n = badd2(__byte_perm(n2[it], n2[it + 1], 0x5410), __byte_perm(n2[it], n2[it + 1], 0x7632));
      n = badd2(n, __shfl_xor_sync(0xffffffffu, n, 1));
      n = badd2(n, __shfl_xor_sync(0xffffffffu, n, 2));
      n = badd2(n, __shfl_xor_sync(0xffffffffu, n, 4));
      n = badd2(n, __shfl_xor_sync(0xffffffffu, n, 8));
      kb2 = bmax2_nan(kb2, n);
    }
  }
}
__device__ __forceinline__ uint32_t warp_max_bits(uint32_t m2) {
  return __reduce_max_sync(0xffffffffu, max((m2 << 16) & 0x7fff0000u, m2 & 0x7fff0000u));
}
__device__ __forceinline__ void publish(int head, uint32_t rows, uint32_t kbest, uint32_t vbest) {
  asm volatile("red.relaxed.gpu.global.max.u32 [%0], %1;" ::"l"(g_kn2 + head), "r"(kbest) : "memory");
  asm volatile("red.relaxed.gpu.global.max.u32 [%0], %1;" ::"l"(g_vmax + head), "r"(vbest) : "memory");
  asm volatile("red.release.gpu.global.add.u32 [%0], %1;" ::"l"(g_ready + head), "r"(rows) : "memory");
}
__device__ __forceinline__ uint32_t ld_acquire(const uint32_t* p) {
  uint32_t v; asm volatile("ld.acquire.gpu.global.u32 %0, [%1];" : "=r"(v) : "l"(p) : "memory"); return v;
}
__device__ __forceinline__ uint32_t ld_relaxed(const uint32_t* p) {
  uint32_t v; asm volatile("ld.relaxed.gpu.global.u32 %0, [%1];" : "=r"(v) : "l"(p) : "memory"); return v;
}

__device__ __forceinline__ void mbar_init(uint32_t bar, uint32_t count) {
  asm volatile("mbarrier.init.shared::cta.b64 [%0], %1;" ::"r"(bar), "r"(count) : "memory");
}
__device__ __forceinline__ void mbar_expect_tx(uint32_t bar, uint32_t bytes) {
  asm volatile("mbarrier.arrive.expect_tx.shared::cta.b64 _, [%0], %1;" ::"r"(bar), "r"(bytes) : "memory");
}
__device__ __forceinline__ void mbar_arrive(uint32_t bar) {
  asm volatile("mbarrier.arrive.shared::cta.b64 _, [%0];" ::"r"(bar) : "memory");
}
__device__ __forceinline__ void mbar_wait(uint32_t bar, uint32_t parity) {
  asm volatile(
      "{\n"
      ".reg .pred p;\n"
      "WAIT_LOOP:\n"
      "mbarrier.try_wait.parity.shared::cta.b64 p, [%0], %1;\n"
      "@p bra.uni WAIT_DONE;\n"
      "bra.uni WAIT_LOOP;\n"
      "WAIT_DONE:\n"
      "}\n" ::"r"(bar), "r"(parity) : "memory");
}
__device__ __forceinline__ void bulk_load(uint32_t dst, const void* src, uint32_t bytes, uint32_t bar) {
  asm volatile("cp.async.bulk.shared::cluster.global.mbarrier::complete_tx::bytes [%0], [%1], %2, [%3];"
               ::"r"(dst), "l"(src), "r"(bytes), "r"(bar) : "memory");
}
__device__ __forceinline__ void bulk_load_mc(uint32_t dst, const void* src, uint32_t bytes, uint32_t bar) {
  asm volatile("cp.async.bulk.shared::cluster.global.mbarrier::complete_tx::bytes.multicast::cluster [%0], [%1], %2, [%3], %4;"
               ::"r"(dst), "l"(src), "r"(bytes), "r"(bar), "h"((uint16_t)3) : "memory");
}
__device__ __forceinline__ void mbar_arrive_cluster(uint32_t bar) {
  asm volatile("mbarrier.arrive.shared::cluster.b64 _, [%0];" ::"r"(bar) : "memory");
}
__device__ __forceinline__ void cluster_arrive() { asm volatile("barrier.cluster.arrive.relaxed.aligned;" ::: "memory"); }
__device__ __forceinline__ void cluster_wait() { asm volatile("barrier.cluster.wait.acquire.aligned;" ::: "memory"); }
__device__ __forceinline__ void wg_fence() { asm volatile("wgmma.fence.sync.aligned;" ::: "memory"); }
__device__ __forceinline__ void wg_commit() { asm volatile("wgmma.commit_group.sync.aligned;" ::: "memory"); }
template <int N> __device__ __forceinline__ void wg_wait() { asm volatile("wgmma.wait_group.sync.aligned %0;" ::"n"(N) : "memory"); }
__device__ __forceinline__ void bar_sync(int id) { asm volatile("bar.sync %0, 256;" ::"r"(id) : "memory"); }
__device__ __forceinline__ void bar_arrive(int id) { asm volatile("bar.arrive %0, 256;" ::"r"(id) : "memory"); }

#define A8(d, o) "+f"(d[o + 0]), "+f"(d[o + 1]), "+f"(d[o + 2]), "+f"(d[o + 3]), "+f"(d[o + 4]), "+f"(d[o + 5]), "+f"(d[o + 6]), "+f"(d[o + 7])
#define ACC64(d) A8(d, 0), A8(d, 8), A8(d, 16), A8(d, 24), A8(d, 32), A8(d, 40), A8(d, 48), A8(d, 56)
#define REGS64                                                                                \
  "{%0, %1, %2, %3, %4, %5, %6, %7, %8, %9, %10, %11, %12, %13, %14, %15, "                   \
  "%16, %17, %18, %19, %20, %21, %22, %23, %24, %25, %26, %27, %28, %29, %30, %31, "          \
  "%32, %33, %34, %35, %36, %37, %38, %39, %40, %41, %42, %43, %44, %45, %46, %47, "          \
  "%48, %49, %50, %51, %52, %53, %54, %55, %56, %57, %58, %59, %60, %61, %62, %63}"

template <int TB>
__device__ __forceinline__ void mma_rs(float (&d)[64], uint32_t a0, uint32_t a1, uint32_t a2, uint32_t a3,
                                       uint64_t desc, int scale_d) {
  asm volatile(
      "{\n.reg .pred p;\nsetp.ne.b32 p, %69, 0;\n"
      "wgmma.mma_async.sync.aligned.m64n128k16.f32.bf16.bf16 " REGS64
      ", {%64, %65, %66, %67}, %68, p, 1, 1, %70;\n}\n"
      : ACC64(d)
      : "r"(a0), "r"(a1), "r"(a2), "r"(a3), "l"(desc), "r"(scale_d), "n"(TB));
}
__device__ __forceinline__ void fence_regs(float (&d)[64]) {
#pragma unroll
  for (int i = 0; i < 64; i++) asm volatile("" : "+f"(d[i])::"memory");
}
__device__ __forceinline__ void fence_regs_u(uint32_t (&d)[32]) {
#pragma unroll
  for (int i = 0; i < 32; i++) asm volatile("" : "+r"(d[i])::"memory");
}

__device__ __forceinline__ uint64_t make_desc(uint32_t addr, uint32_t lbo_bytes) {
  return (uint64_t)((addr & 0x3FFFF) >> 4) | ((uint64_t)(lbo_bytes >> 4) << 16) | ((uint64_t)(1024 >> 4) << 32) |
         ((uint64_t)1 << 62);
}

__device__ __forceinline__ void issue_qk(float (&S)[64], const uint32_t (&Q)[32], uint32_t kaddr) {
  const uint64_t d0 = make_desc(kaddr, 16);
#pragma unroll
  for (int kk = 0; kk < 8; kk++) {
    const uint64_t off = (uint64_t)(((kk >> 2) * 16384 + (kk & 3) * 32) >> 4);
    mma_rs<0>(S, Q[kk * 4 + 0], Q[kk * 4 + 1], Q[kk * 4 + 2], Q[kk * 4 + 3], d0 + off, kk != 0);
  }
}
__device__ __forceinline__ void issue_pv(float (&O)[64], const uint32_t (&P)[32], uint32_t vaddr, int acc) {
  const uint64_t d0 = make_desc(vaddr, 16384);
#pragma unroll
  for (int kk = 0; kk < 8; kk++)
    mma_rs<1>(O, P[kk * 4 + 0], P[kk * 4 + 1], P[kk * 4 + 2], P[kk * 4 + 3], d0 + (uint64_t)((kk * 2048) >> 4),
              kk == 0 ? acc : 1);
}

__device__ __forceinline__ void tma_load_2d(uint32_t dst, const CUtensorMap* tm, int c0, int c1, uint32_t bar) {
  asm volatile("cp.async.bulk.tensor.2d.shared::cluster.global.mbarrier::complete_tx::bytes [%0], [%1, {%3, %4}], [%2];"
               ::"r"(dst), "l"(tm), "r"(bar), "r"(c0), "r"(c1) : "memory");
}
__device__ __forceinline__ void load_q(uint32_t (&Q)[32], uint32_t qaddr) {
#pragma unroll
  for (int kk = 0; kk < 8; kk++)
    asm volatile("ldmatrix.sync.aligned.m8n8.x4.shared.b16 {%0, %1, %2, %3}, [%4];"
                 : "=r"(Q[kk * 4 + 0]), "=r"(Q[kk * 4 + 1]), "=r"(Q[kk * 4 + 2]), "=r"(Q[kk * 4 + 3])
                 : "r"((qaddr ^ ((kk & 3) << 5)) + (kk >> 2) * 16384) : "memory");
}

__device__ __forceinline__ float q_norm(const uint32_t (&Q)[32]) {
  uint32_t a0 = 0, a1 = 0, b0 = 0, b1 = 0;
#pragma unroll
  for (int i = 0; i < 8; i++) {
    a0 = bfma2(Q[4 * i + 0], Q[4 * i + 0], a0);
    a1 = bfma2(Q[4 * i + 2], Q[4 * i + 2], a1);
    b0 = bfma2(Q[4 * i + 1], Q[4 * i + 1], b0);
    b1 = bfma2(Q[4 * i + 3], Q[4 * i + 3], b1);
  }
  float n0 = (bf_lo(a0) + bf_hi(a0)) + (bf_lo(a1) + bf_hi(a1));
  float n1 = (bf_lo(b0) + bf_hi(b0)) + (bf_lo(b1) + bf_hi(b1));
  n0 += __shfl_xor_sync(0xffffffffu, n0, 1);
  n1 += __shfl_xor_sync(0xffffffffu, n1, 1);
  n0 += __shfl_xor_sync(0xffffffffu, n0, 2);
  n1 += __shfl_xor_sync(0xffffffffu, n1, 2);
  const uint32_t m = max(__float_as_uint(n0) & 0x7fffffffu, __float_as_uint(n1) & 0x7fffffffu);
  const float n = __uint_as_float(__reduce_max_sync(0xffffffffu, m));
  return fmaf(n, 1.06f, 1e-30f);
}
__device__ __forceinline__ float lds_f32(uint32_t addr) {
  float v; asm volatile("ld.shared.f32 %0, [%1];" : "=f"(v) : "r"(addr) : "memory"); return v;
}

__global__ void __cluster_dims__(2, 1, 1) __launch_bounds__(384, 1) attn_kernel(const __grid_constant__ CUtensorMap tmap_q, const __grid_constant__ DeqArgs deq,
                                                      __nv_bfloat16* __restrict__ out, int first_helper) {
  extern __shared__ uint8_t smem_raw[];
  const uint32_t smem_base = (smem_u32(smem_raw) + 1023u) & ~1023u;
  const uint32_t q_smem = smem_base + NSLOT * TILE_BYTES;
  const uint32_t bar_full = q_smem + TILE_BYTES;
  const uint32_t bar_empty = bar_full + 8 * NSLOT;
  const uint32_t bar_peer = bar_empty + 8 * NSLOT;
  const uint32_t bar_qfull = bar_peer + 8 * NSLOT;
  const uint32_t bar_qempty = bar_qfull + 8;
  const uint32_t bar_meta = bar_qempty + 8;
  const uint32_t meta_smem = bar_meta + 8;
  const uint32_t red_smem = bar_full + 512;
  const int tid = threadIdx.x;
  const int warp = __shfl_sync(0xffffffffu, tid >> 5, 0);
  const int lane = tid & 31;
  TR3C(0);
  if (warp != 8) cluster_arrive();

  if (warp < 8) {
    uint32_t kb2 = 0, vb2 = 0, rows = 0;
    for (int u = (int)blockIdx.x * 8 + warp; u < 2 * SEQ / 4; u += (int)gridDim.x * 8) {
      dequant_unit<2>(deq, 0, u >= SEQ / 4, (u & (SEQ / 4 - 1)) * 4, lane, kb2, vb2);
      rows += 4;
    }
    TR3C(2);
    const uint32_t kbest = warp_max_bits(kb2), vbest = warp_max_bits(vb2);
    if (lane == 0) asm volatile("st.shared.v4.u32 [%0], {%1, %2, %3, %3};" ::"r"(red_smem + 16 * warp), "r"(kbest), "r"(vbest), "r"(rows) : "memory");
  } else if (tid == 256) {
    asm volatile("prefetch.tensormap [%0];" ::"l"(&tmap_q) : "memory");
#pragma unroll
    for (int s = 0; s < NSLOT; s++) {
      mbar_init(bar_full + 8 * s, 1);
      mbar_init(bar_empty + 8 * s, 8);
      mbar_init(bar_peer + 8 * s, 1);
    }
    mbar_init(bar_qfull, 1);
    mbar_init(bar_qempty, 8);
    mbar_init(bar_meta, 1);
    asm volatile("fence.mbarrier_init.release.cluster;" ::: "memory");
  }
  if (warp == 8) { __syncwarp(); cluster_arrive(); }
  __syncthreads();
  TR3C(1);
  if (warp == 8) {
    uint32_t k = 0, v = 0, n = 0;
    if (lane < 8) {
      asm volatile("ld.shared.v2.u32 {%0, %1}, [%2];" : "=r"(k), "=r"(v) : "r"(red_smem + 16 * lane) : "memory");
      asm volatile("ld.shared.u32 %0, [%1];" : "=r"(n) : "r"(red_smem + 16 * lane + 8) : "memory");
    }
    k = __reduce_max_sync(0xffffffffu, k);
    v = __reduce_max_sync(0xffffffffu, v);
    n = __reduce_add_sync(0xffffffffu, n);
    if (lane == 0 && n) publish(0, n, k, v);
    __syncwarp();
  }

  if ((int)blockIdx.x >= first_helper) {
    const int nh = (int)gridDim.x - first_helper, hb = (int)blockIdx.x - first_helper;
    constexpr int UPH = 2 * SEQ / 16;
    int buf = 1;
    __syncthreads();
#pragma unroll 1
    for (int u0 = 0; u0 < (HKV - 1) * UPH; u0 += 12 * nh, buf ^= 1) {
      const int u = u0 + warp * nh + hb;
      uint32_t kb2 = 0, vb2 = 0, rows = 0;
      const int head = 1 + u / UPH;
      if (u < (HKV - 1) * UPH) {
        const int w = u % UPH;
        dequant_unit<8>(deq, head, w >= UPH / 2, (w & (UPH / 2 - 1)) * 16, lane, kb2, vb2);
        rows = 16;
      }
      const uint32_t kbest = warp_max_bits(kb2), vbest = warp_max_bits(vb2);
      const uint32_t red = red_smem + buf * 192;
      if (lane == 0) asm volatile("st.shared.v4.u32 [%0], {%1, %2, %3, %4};" ::"r"(red + 16 * warp), "r"(kbest), "r"(vbest), "r"(rows), "r"(head) : "memory");
      __syncthreads();
      if (warp == 9 + buf) {
        uint32_t k = 0, v = 0, n = 0, hd = 0;
        if (lane < 12) asm volatile("ld.shared.v4.u32 {%0, %1, %2, %3}, [%4];" : "=r"(k), "=r"(v), "=r"(n), "=r"(hd) : "r"(red + 16 * lane) : "memory");
        for (int h = 1; h < HKV; h++) {
          const bool m = (int)hd == h;
          const uint32_t hk = __reduce_max_sync(0xffffffffu, m ? k : 0u), hv = __reduce_max_sync(0xffffffffu, m ? v : 0u);
          const uint32_t hn = __reduce_add_sync(0xffffffffu, m ? n : 0u);
          if (lane == 0 && hn) publish(h, hn, hk, hv);
        }
        __syncwarp();
      }
    }
    __syncthreads();
  }

  cluster_wait();
  if (warp >= 8) {
    asm volatile("setmaxnreg.dec.sync.aligned.u32 56;");
    if (warp == 8) {
      if (lane == 0) {
        const int ntile = (NTILES - (int)blockIdx.x + (int)gridDim.x - 1) / (int)gridDim.x;
        const int total = ntile * NBLK;
        auto load_qtile = [&](int r) {
          const int row = ((int)blockIdx.x + r * (int)gridDim.x) * TILE_M;
          mbar_expect_tx(bar_qfull, TILE_BYTES);
          tma_load_2d(q_smem, &tmap_q, 0, row, bar_qfull);
          tma_load_2d(q_smem + 16384, &tmap_q, 64, row, bar_qfull);
        };
        auto wait_head = [&](int r) {
          const uint32_t* flag = g_ready + ((int)blockIdx.x + r * (int)gridDim.x) / TILES_PER_KVH;
          while (ld_acquire(flag) < 2 * SEQ) {}
          asm volatile("fence.proxy.async;" ::: "memory");
        };
        auto post_meta = [&](int r) {
          const int h = ((int)blockIdx.x + r * (int)gridDim.x) / TILES_PER_KVH;
          const uint32_t k = ld_relaxed(g_kn2 + h), v = ld_relaxed(g_vmax + h);
          float kn2 = fmaf(__uint_as_float(k), 1.03f, 1e-30f);
          if (v < VMAX_LO || v > VMAX_HI) kn2 = INFINITY;
          asm volatile("st.shared.f32 [%0], %1;" ::"r"(meta_smem + 4 * (r & 1)), "f"(kn2) : "memory");
          mbar_arrive(bar_meta);
        };
        load_qtile(0);
        TR3(2, 2);
        wait_head(0);
        TR3(2, 3);
        int slot = 0;
        uint32_t phase = 1;
        const uint32_t half = (blockIdx.x & 1) * (TILE_BYTES / 2);
        uint32_t peer_c;
        asm volatile("mapa.shared::cluster.u32 %0, %1, %2;" : "=r"(peer_c) : "r"(bar_peer), "r"((blockIdx.x & 1) ^ 1));
        bool warm = false;
        const uint8_t* kbase = g_kv;
        const uint8_t* vbase = g_kv + (size_t)HKV * NBLK * TILE_BYTES;
        auto load = [&](const uint8_t* base, int it) {
          const int u = (int)blockIdx.x + (it >> 4) * (int)gridDim.x;
          const uint8_t* src = base + (size_t)((u / TILES_PER_KVH) * NBLK + (it & 15)) * TILE_BYTES;
          mbar_wait(bar_empty + 8 * slot, phase);
          if (warm) mbar_arrive_cluster(peer_c + 8 * slot);
          mbar_wait(bar_peer + 8 * slot, phase);
          mbar_expect_tx(bar_full + 8 * slot, TILE_BYTES);
          bulk_load_mc(smem_base + slot * TILE_BYTES + half, src + half, TILE_BYTES / 2, bar_full + 8 * slot);
          if (++slot == NSLOT) { slot = 0; phase ^= 1; warm = true; }
        };
        auto retire = [&]() {
          uint32_t n;
          asm volatile("atom.acq_rel.gpu.global.add.u32 %0, [%1], 1;" : "=r"(n) : "l"(&g_done) : "memory");
          if (n == gridDim.x - 1) {
#pragma unroll
            for (int h = 0; h < HKV; h++) { g_ready[h] = 0; g_kn2[h] = 0; g_vmax[h] = 0; }
            g_done = 0;
          }
        };
        load(kbase, 0);
        TR3(2, 4);
        post_meta(0);
        if (ntile == 1) retire();
        for (int it = 0; it < total - 1; it++) {
          if ((it & 15) == 10 && (it >> 4) + 1 < ntile) {
            wait_head((it >> 4) + 1);
            post_meta((it >> 4) + 1);
            if ((it >> 4) + 2 == ntile) retire();
            mbar_wait(bar_qempty, (it >> 4) & 1);
            load_qtile((it >> 4) + 1);
          }
          load(kbase, it + 1);
          load(vbase, it);
        }
        load(vbase, total - 1);
      }
    }
  } else {
    asm volatile("setmaxnreg.inc.sync.aligned.u32 224;");
    TR3C(5);
    const int ntile = (NTILES - (int)blockIdx.x + (int)gridDim.x - 1) / (int)gridDim.x;
    const int total = ntile * NBLK;
    const int wg = warp >> 2;
    const int g = lane >> 2, c = lane & 3;
    const int row0 = wg * 64 + (warp & 3) * 16;
    __nv_bfloat16* optr = out + ((size_t)blockIdx.x * TILE_M + row0 + g) * DH + c * 8;
    const uint32_t q_lane = q_smem + (row0 + (lane & 15)) * 128 + (((lane >> 4) ^ (lane & 7)) << 4);

    float S[64], O[64];
    uint32_t P[32], Q[32];
    float l0 = 0.f, l1 = 0.f, m0 = -INFINITY, m1 = -INFINITY;
    float lf0 = 0.f, lf1 = 0.f;
    int slot = 0;
    uint32_t phase = 0;
    auto advance = [&]() { if (++slot == NSLOT) { slot = 0; phase ^= 1; } };

    TRACE_PT(0);
    mbar_wait(bar_qfull, 0);
    TR3C(6);
    load_q(Q, q_lane);
    __syncwarp();
    if (lane == 0) mbar_arrive(bar_qempty);
    const float qn_first = q_norm(Q);
    bool fast;

    float al0 = 1.f, al1 = 1.f;
    bool resc = false;
    auto softmax = [&]() {
      if (fast) {
#pragma unroll
        for (int i = 0; i < 64; i += 4) {
          S[i + 0] = ex2(S[i + 0]); S[i + 1] = ex2(S[i + 1]);
          S[i + 2] = ex2(S[i + 2]); S[i + 3] = ex2(S[i + 3]);
          l0 += S[i + 0]; l1 += S[i + 2];
          l0 += S[i + 1]; l1 += S[i + 3];
        }
      } else {
        float x0 = fmaxf(S[0], S[1]), x1 = fmaxf(S[2], S[3]);
#pragma unroll
        for (int i = 4; i < 64; i += 4) {
          x0 = fmaxf(x0, fmaxf(S[i + 0], S[i + 1]));
          x1 = fmaxf(x1, fmaxf(S[i + 2], S[i + 3]));
        }
        x0 = fmaxf(x0, __shfl_xor_sync(0xffffffffu, x0, 1));
        x1 = fmaxf(x1, __shfl_xor_sync(0xffffffffu, x1, 1));
        x0 = fmaxf(x0, __shfl_xor_sync(0xffffffffu, x0, 2));
        x1 = fmaxf(x1, __shfl_xor_sync(0xffffffffu, x1, 2));
        const bool need = (x0 > m0 + 8.f) || (x1 > m1 + 8.f);
        resc = __any_sync(0xffffffffu, need);
        if (resc) {
          const float n0 = fmaxf(m0, x0), n1 = fmaxf(m1, x1);
          al0 = (n0 == -INFINITY) ? 1.f : ex2(m0 - n0);
          al1 = (n1 == -INFINITY) ? 1.f : ex2(m1 - n1);
          m0 = n0; m1 = n1;
          l0 *= al0; l1 *= al1;
        }
        const float s0 = (m0 == -INFINITY) ? 0.f : m0, s1 = (m1 == -INFINITY) ? 0.f : m1;
#pragma unroll
        for (int i = 0; i < 64; i += 4) {
          S[i + 0] = ex2(S[i + 0] - s0); S[i + 1] = ex2(S[i + 1] - s0);
          S[i + 2] = ex2(S[i + 2] - s1); S[i + 3] = ex2(S[i + 3] - s1);
          l0 += S[i + 0]; l1 += S[i + 2];
          l0 += S[i + 1]; l1 += S[i + 3];
        }
      }
    };
    auto pack_p = [&]() {
#pragma unroll
      for (int i = 0; i < 32; i++) P[i] = pack_bf16(S[2 * i], S[2 * i + 1]);
    };
    auto finish_l = [&](float& e0, float& e1) {
      e0 += __shfl_xor_sync(0xffffffffu, e0, 1);
      e1 += __shfl_xor_sync(0xffffffffu, e1, 1);
      e0 += __shfl_xor_sync(0xffffffffu, e0, 2);
      e1 += __shfl_xor_sync(0xffffffffu, e1, 2);
      asm("rcp.approx.ftz.f32 %0, %0;" : "+f"(e0));
      asm("rcp.approx.ftz.f32 %0, %0;" : "+f"(e1));
    };
    auto epilogue = [&](float r0, float r1) {
#pragma unroll
      for (int J = 0; J < 4; J++) {
        float* o = &O[16 * J];
        const uint32_t a0 = pack_bf16(o[0] * r0, o[1] * r0), a1 = pack_bf16(o[4] * r0, o[5] * r0);
        const uint32_t b0 = pack_bf16(o[2] * r1, o[3] * r1), b1 = pack_bf16(o[6] * r1, o[7] * r1);
        const uint32_t a2 = pack_bf16(o[8] * r0, o[9] * r0), a3 = pack_bf16(o[12] * r0, o[13] * r0);
        const uint32_t b2 = pack_bf16(o[10] * r1, o[11] * r1), b3 = pack_bf16(o[14] * r1, o[15] * r1);
        o[0] = __uint_as_float(a0); o[1] = __uint_as_float(a1); o[2] = __uint_as_float(a2); o[3] = __uint_as_float(a3);
        o[4] = __uint_as_float(b0); o[5] = __uint_as_float(b1); o[6] = __uint_as_float(b2); o[7] = __uint_as_float(b3);
        asm volatile("st.global.v4.f32 [%0], {%1, %2, %3, %4};" ::"l"(optr + J * 32), "f"(o[0]), "f"(o[1]), "f"(o[2]), "f"(o[3]) : "memory");
        asm volatile("st.global.v4.f32 [%0], {%1, %2, %3, %4};" ::"l"(optr + 8 * DH + J * 32), "f"(o[4]), "f"(o[5]), "f"(o[6]), "f"(o[7]) : "memory");
      }
    };

    if (wg == 1) bar_arrive(1);
    TR3C(7);
    mbar_wait(bar_full + 8 * slot, phase);
    TR3C(8);
    wg_fence();
    issue_qk(S, Q, smem_base + slot * TILE_BYTES);
    wg_commit();
    mbar_wait(bar_meta, 0);
    fast = qn_first * lds_f32(meta_smem) <= FAST_BOUND2;
    TR3C(9);
    wg_wait<0>();
    fence_regs(S);
    TR3C(10);
    if (lane == 0) mbar_arrive(bar_empty + 8 * slot);
    advance();
    softmax();
    TR3C(11);
    pack_p();
    TR3C(12);

    for (int it = 0; it < total - 1; it++) {
      const int j = it & 15;
      const int kslot = slot;
      const uint32_t kphase = phase;
      advance();
      const int vslot = slot;
      const uint32_t vphase = phase;
      advance();

      TRACE_PT(it + 1);
      TR2(0);
      bar_sync(1 + wg);
      TR2(1);
      mbar_wait(bar_full + 8 * kslot, kphase);
      mbar_wait(bar_full + 8 * vslot, vphase);
      wg_fence();
      issue_qk(S, Q, smem_base + kslot * TILE_BYTES);
      wg_commit();
      TR2(2);
      if (j == 15) {
        mbar_wait(bar_meta, ((it >> 4) + 1) & 1);
        fast = q_norm(Q) * lds_f32(meta_smem + 4 * (((it >> 4) + 1) & 1)) <= FAST_BOUND2;
        lf0 = l0; lf1 = l1;
        finish_l(lf0, lf1);
        l0 = 0.f; l1 = 0.f; m0 = -INFINITY; m1 = -INFINITY;
      } else if (j == 0 && it != 0) {
        epilogue(lf0, lf1);
        optr += (size_t)gridDim.x * TILE_M * DH;
      }
      wg_fence();
      issue_pv(O, P, smem_base + vslot * TILE_BYTES, j != 0);
      wg_commit();
      TR2(3);
      bar_arrive(2 - wg);

      wg_wait<1>();
      fence_regs(S);
      TR2(4);
      if (lane == 0) mbar_arrive(bar_empty + 8 * kslot);
      if (j == 14 && it + 2 < total) {
        mbar_wait(bar_qfull, ((it >> 4) + 1) & 1);
        load_q(Q, q_lane);
        __syncwarp();
        if (lane == 0) mbar_arrive(bar_qempty);
      }
      resc = false;
      softmax();
      TR2(5);
      wg_wait<0>();
      fence_regs(O);
      fence_regs_u(P);
      TR2(6);
      if (lane == 0) mbar_arrive(bar_empty + 8 * vslot);
      if (resc && j != 15) {
#pragma unroll
        for (int i = 0; i < 64; i += 4) {
          O[i + 0] *= al0; O[i + 1] *= al0; O[i + 2] *= al1; O[i + 3] *= al1;
        }
      }
      pack_p();
      TR2(7);
    }
    bar_sync(1 + wg);
    mbar_wait(bar_full + 8 * slot, phase);
    wg_fence();
    issue_pv(O, P, smem_base + slot * TILE_BYTES, 1);
    wg_commit();
    if (wg == 0) bar_arrive(2);
    wg_wait<0>();
    fence_regs(O);
    finish_l(l0, l1);
    epilogue(l0, l1);
    TRACE_PT(65);
    __syncwarp();
    cluster_arrive();
    cluster_wait();
  }
}

}

extern "C" void kernel_launch(void* const* d_in, const int* in_sizes, int n_in, void* d_out, int out_size) {
  const __nv_bfloat16* q = (const __nv_bfloat16*)d_in[0];
  const int* qk = (const int*)d_in[1];
  const int* qv = (const int*)d_in[2];
  const __nv_bfloat16* ks = (const __nv_bfloat16*)d_in[3];
  const __nv_bfloat16* kz = (const __nv_bfloat16*)d_in[4];
  const __nv_bfloat16* vs = (const __nv_bfloat16*)d_in[5];
  const __nv_bfloat16* vz = (const __nv_bfloat16*)d_in[6];
  __nv_bfloat16* out = (__nv_bfloat16*)d_out;

  typedef CUresult (*EncodeFn)(CUtensorMap*, CUtensorMapDataType, cuuint32_t, void*, const cuuint64_t*, const cuuint64_t*,
                               const cuuint32_t*, const cuuint32_t*, CUtensorMapInterleave, CUtensorMapSwizzle,
                               CUtensorMapL2promotion, CUtensorMapFloatOOBfill);
  static int num_sms = 0;
  static EncodeFn encode = nullptr;
  if (num_sms == 0) {
    int dev = 0;
    cudaGetDevice(&dev);
    cudaDeviceGetAttribute(&num_sms, cudaDevAttrMultiProcessorCount, dev);
    cudaFuncSetAttribute(attn_kernel, cudaFuncAttributeMaxDynamicSharedMemorySize, SMEM_BYTES);
    void* fn = nullptr;
    cudaDriverEntryPointQueryResult qres;
    cudaGetDriverEntryPoint("cuTensorMapEncodeTiled", &fn, cudaEnableDefault, &qres);
    encode = (EncodeFn)fn;
    cudaLaunchConfig_t cfg = {};
    cfg.gridDim = dim3((unsigned)(num_sms & ~1)); cfg.blockDim = dim3(384); cfg.dynamicSmemBytes = SMEM_BYTES;
    cudaLaunchAttribute attr; attr.id = cudaLaunchAttributeClusterDimension;
    attr.val.clusterDim.x = 2; attr.val.clusterDim.y = 1; attr.val.clusterDim.z = 1;
    cfg.attrs = &attr; cfg.numAttrs = 1;
    int ncl = 0;
    cudaError_t e = cudaOccupancyMaxActiveClusters(&ncl, attn_kernel, &cfg);
    if (e == cudaSuccess && ncl > 0 && 2 * ncl < num_sms) num_sms = 2 * ncl;
    num_sms &= ~1;
  }
  CUtensorMap tmap_q;
  {
    const cuuint64_t gdim[2] = {(cuuint64_t)DH, (cuuint64_t)ROWS};
    const cuuint64_t gstride[1] = {(cuuint64_t)DH * 2};
    const cuuint32_t box[2] = {64, (cuuint32_t)TILE_M};
    const cuuint32_t estride[2] = {1, 1};
    encode(&tmap_q, CU_TENSOR_MAP_DATA_TYPE_BFLOAT16, 2, (void*)q, gdim, gstride, box, estride, CU_TENSOR_MAP_INTERLEAVE_NONE,
           CU_TENSOR_MAP_SWIZZLE_128B, CU_TENSOR_MAP_L2_PROMOTION_L2_256B, CU_TENSOR_MAP_FLOAT_OOB_FILL_NONE);
  }
  DeqArgs deq{qk, qv, ks, kz, vs, vz, q};
  int grid = num_sms < NTILES ? num_sms : NTILES;
  int first_helper = NTILES % grid;
  if (grid - first_helper < 8) first_helper = 0;
  attn_kernel<<<grid, 384, SMEM_BYTES>>>(tmap_q, deq, out, first_helper);
}
```

```cpp
#include <cuda_runtime.h>
#include <cuda.h>
#include <cuda_bf16.h>
#include <stdint.h>

namespace {

constexpr int HQ = 32, HKV = 4, SEQ = 2048, DH = 128;
constexpr int BLK = 128;
constexpr int NBLK = SEQ / BLK;
constexpr int TILE_BYTES = BLK * DH * 2;
constexpr int ROWS = HQ * SEQ;
constexpr int TILE_M = 128;
constexpr int NTILES = ROWS / TILE_M;
constexpr int TILES_PER_KVH = NTILES / HKV;
constexpr int NSLOT = 6;
constexpr int NSPLIT = 52;
constexpr int QDELAY = 400;
constexpr int RDELAY = 2000;
constexpr int QDELAY2 = 400;
constexpr int SMEM_BYTES = (NSLOT + 1) * TILE_BYTES + 1024 + 256 + 1024;

constexpr float LSUM_LO = 9.094947017729282e-13f;
constexpr float LSUM_HI = 1.152921504606847e18f;
constexpr uint32_t VMAX_LO = 0x2B800000u;
constexpr uint32_t VMAX_HI = 0x5D800000u;

__device__ __align__(1024) uint8_t g_kv[2 * HKV * NBLK * TILE_BYTES];
constexpr int STAGE_BLKS = 6, STAGE_ROWS = STAGE_BLKS * BLK, NSTAGE = 2;
constexpr int HEAD0_REST = 2 * SEQ - NSTAGE * STAGE_ROWS;
constexpr int NREP = 4, RSTRIDE = 16;
__device__ __align__(128) unsigned long long g_ready[(HKV + NSTAGE) * NREP * RSTRIDE];
__device__ uint32_t g_done;

__device__ __forceinline__ uint32_t smem_u32(const void* p) { return (uint32_t)__cvta_generic_to_shared(p); }

__device__ __forceinline__ uint32_t pack_bf16(float lo, float hi) {
  uint32_t r;
  asm("cvt.rn.bf16x2.f32 %0, %1, %2;" : "=r"(r) : "f"(hi), "f"(lo));
  return r;
}
__device__ __forceinline__ uint32_t bsub2(uint32_t a, uint32_t b) {
  uint32_t r; asm("sub.rn.bf16x2 %0, %1, %2;" : "=r"(r) : "r"(a), "r"(b)); return r;
}
__device__ __forceinline__ uint32_t bmul2(uint32_t a, uint32_t b) {
  uint32_t r; asm("mul.rn.bf16x2 %0, %1, %2;" : "=r"(r) : "r"(a), "r"(b)); return r;
}
__device__ __forceinline__ uint32_t bfma2(uint32_t a, uint32_t b, uint32_t c) {
  uint32_t r; asm("fma.rn.bf16x2 %0, %1, %2, %3;" : "=r"(r) : "r"(a), "r"(b), "r"(c)); return r;
}
__device__ __forceinline__ float ex2(float x) {
  float y; asm("ex2.approx.ftz.f32 %0, %1;" : "=f"(y) : "f"(x)); return y;
}

struct DeqArgs {
  const int* qk; const int* qv;
  const __nv_bfloat16* ks; const __nv_bfloat16* kz; const __nv_bfloat16* vs; const __nv_bfloat16* vz;
  __nv_bfloat16* out;
};
__device__ __forceinline__ uint32_t bmaxabs2_nan(uint32_t a, uint32_t b) {
  uint32_t r; asm("max.NaN.xorsign.abs.bf16x2 %0, %1, %2;" : "=r"(r) : "r"(a), "r"(b)); return r;
}
constexpr uint32_t KSCALE_HI2 = 0x3e033e03u, KSCALE_LO2 = 0xb9d8b9d8u;

template <int NSTEP>
__device__ __forceinline__ void dequant_unit(const DeqArgs& a, int head, int isV, int tok0, int lane, uint32_t& vb2) {
  tok0 += lane >> 4;
  const int ch = lane & 15, blk = tok0 >> 7;
  const int row0 = head * SEQ + tok0;
  uint8_t* img = g_kv + (size_t)((isV * HKV + head) * NBLK + blk) * TILE_BYTES + (ch >> 3) * 16384;
  if (isV) {
    const int* src = a.qv + (size_t)row0 * DH + 8 * ch;
    int4 v[NSTEP][2];
    uint32_t s1[NSTEP], z1[NSTEP];
#pragma unroll
    for (int it = 0; it < NSTEP; it++) {
      v[it][0] = __ldg(reinterpret_cast<const int4*>(src + it * 2 * DH));
      v[it][1] = __ldg(reinterpret_cast<const int4*>(src + it * 2 * DH + 4));
    }
#pragma unroll
    for (int it = 0; it < NSTEP; it++) {
      s1[it] = __bfloat16_as_ushort(__ldg(a.vs + row0 + it * 2));
      z1[it] = __bfloat16_as_ushort(__ldg(a.vz + row0 + it * 2));
    }
#pragma unroll
    for (int it = 0; it < NSTEP; it++) {
      const int t = (row0 + it * 2) & (BLK - 1);
      const uint32_t s2 = s1[it] * 0x10001u, z2 = z1[it] * 0x10001u;
      const int x[8] = {v[it][0].x, v[it][0].y, v[it][0].z, v[it][0].w, v[it][1].x, v[it][1].y, v[it][1].z, v[it][1].w};
      uint32_t w[4];
#pragma unroll
      for (int c = 0; c < 4; c++) {
        const uint32_t y = pack_bf16(__int2float_rn(x[2 * c]), __int2float_rn(x[2 * c + 1]));
        w[c] = bmul2(bsub2(y, z2), s2);
        vb2 = bmaxabs2_nan(vb2, w[c]);
      }
      *reinterpret_cast<uint4*>(img + t * 128 + (((ch & 7) ^ (t & 7)) << 4)) = make_uint4(w[0], w[1], w[2], w[3]);
    }
  } else {
    const int* src = a.qk + (size_t)row0 * DH + 8 * ch;
    int4 v[NSTEP][2];
#pragma unroll
    for (int it = 0; it < NSTEP; it++) {
      v[it][0] = __ldg(reinterpret_cast<const int4*>(src + it * 2 * DH));
      v[it][1] = __ldg(reinterpret_cast<const int4*>(src + it * 2 * DH + 4));
    }
    const int off = (head * NBLK + blk) * DH + 8 * ch;
    const uint4 s4 = __ldg(reinterpret_cast<const uint4*>(a.ks + off));
    const uint4 z4 = __ldg(reinterpret_cast<const uint4*>(a.kz + off));
#pragma unroll
    for (int it = 0; it < NSTEP; it++) {
      const int t = (row0 + it * 2) & (BLK - 1);
      const int x[8] = {v[it][0].x, v[it][0].y, v[it][0].z, v[it][0].w, v[it][1].x, v[it][1].y, v[it][1].z, v[it][1].w};
      const uint32_t sc[4] = {s4.x, s4.y, s4.z, s4.w}, zr[4] = {z4.x, z4.y, z4.z, z4.w};
      uint32_t w[4];
#pragma unroll
      for (int c = 0; c < 4; c++) {
        uint32_t y = pack_bf16(__int2float_rn(x[2 * c]), __int2float_rn(x[2 * c + 1]));
        y = bmul2(bsub2(y, zr[c]), sc[c]);
        w[c] = bfma2(y, KSCALE_HI2, bmul2(y, KSCALE_LO2));
      }
      *reinterpret_cast<uint4*>(img + t * 128 + (((ch & 7) ^ (t & 7)) << 4)) = make_uint4(w[0], w[1], w[2], w[3]);
    }
  }
}
struct Unit4 { int4 v[2][2]; uint4 s4, z4; };
__device__ __forceinline__ void unit4_load(const DeqArgs& a, int isV, int tok0, int lane, Unit4& U) {
  tok0 += lane >> 4;
  const int ch = lane & 15;
  const int* src = (isV ? a.qv : a.qk) + (size_t)tok0 * DH + 8 * ch;
#pragma unroll
  for (int it = 0; it < 2; it++) {
    asm volatile("ld.global.nc.v4.s32 {%0, %1, %2, %3}, [%4];" : "=r"(U.v[it][0].x), "=r"(U.v[it][0].y), "=r"(U.v[it][0].z), "=r"(U.v[it][0].w) : "l"(src + it * 2 * DH));
    asm volatile("ld.global.nc.v4.s32 {%0, %1, %2, %3}, [%4];" : "=r"(U.v[it][1].x), "=r"(U.v[it][1].y), "=r"(U.v[it][1].z), "=r"(U.v[it][1].w) : "l"(src + it * 2 * DH + 4));
  }
  if (isV) {
    asm volatile("ld.global.nc.u16 %0, [%1];" : "=r"(U.s4.x) : "l"(a.vs + tok0));
    asm volatile("ld.global.nc.u16 %0, [%1];" : "=r"(U.s4.y) : "l"(a.vs + tok0 + 2));
    asm volatile("ld.global.nc.u16 %0, [%1];" : "=r"(U.z4.x) : "l"(a.vz + tok0));
    asm volatile("ld.global.nc.u16 %0, [%1];" : "=r"(U.z4.y) : "l"(a.vz + tok0 + 2));
    U.s4.z = U.s4.w = U.z4.z = U.z4.w = 0;
  } else {
    const int off = (tok0 >> 7) * DH + 8 * ch;
    U.s4 = __ldg(reinterpret_cast<const uint4*>(a.ks + off));
    U.z4 = __ldg(reinterpret_cast<const uint4*>(a.kz + off));
  }
}
__device__ __forceinline__ void unit4_store(const Unit4& U, int isV, int tok0, int lane, uint32_t& vb2) {
  tok0 += lane >> 4;
  const int ch = lane & 15;
  uint8_t* img = g_kv + (size_t)(isV * HKV * NBLK + (tok0 >> 7)) * TILE_BYTES + (ch >> 3) * 16384;
#pragma unroll
  for (int it = 0; it < 2; it++) {
    const int t = (tok0 + it * 2) & (BLK - 1);
    const int x[8] = {U.v[it][0].x, U.v[it][0].y, U.v[it][0].z, U.v[it][0].w, U.v[it][1].x, U.v[it][1].y, U.v[it][1].z, U.v[it][1].w};
    const uint32_t sc[4] = {U.s4.x, U.s4.y, U.s4.z, U.s4.w}, zr[4] = {U.z4.x, U.z4.y, U.z4.z, U.z4.w};
    uint32_t w[4];
#pragma unroll
    for (int c = 0; c < 4; c++) {
      const uint32_t y = pack_bf16(__int2float_rn(x[2 * c]), __int2float_rn(x[2 * c + 1]));
      if (isV) {
        w[c] = bmul2(bsub2(y, (it ? U.z4.y : U.z4.x) * 0x10001u), (it ? U.s4.y : U.s4.x) * 0x10001u);
        vb2 = bmaxabs2_nan(vb2, w[c]);
      } else {
        const uint32_t k = bmul2(bsub2(y, zr[c]), sc[c]);
        w[c] = bfma2(k, KSCALE_HI2, bmul2(k, KSCALE_LO2));
      }
    }
    *reinterpret_cast<uint4*>(img + t * 128 + (((ch & 7) ^ (t & 7)) << 4)) = make_uint4(w[0], w[1], w[2], w[3]);
  }
}
struct K0Unit { int4 v[4][2]; uint4 s4, z4; };
__device__ __forceinline__ void k0_load(const DeqArgs& a, int tok0, int lane, K0Unit& U) {
  const int ch = lane & 15;
  const int* src = a.qk + (size_t)(tok0 + (lane >> 4)) * DH + 8 * ch;
#pragma unroll
  for (int it = 0; it < 4; it++) {
    asm volatile("ld.global.nc.v4.s32 {%0, %1, %2, %3}, [%4];" : "=r"(U.v[it][0].x), "=r"(U.v[it][0].y), "=r"(U.v[it][0].z), "=r"(U.v[it][0].w) : "l"(src + it * 2 * DH));
    asm volatile("ld.global.nc.v4.s32 {%0, %1, %2, %3}, [%4];" : "=r"(U.v[it][1].x), "=r"(U.v[it][1].y), "=r"(U.v[it][1].z), "=r"(U.v[it][1].w) : "l"(src + it * 2 * DH + 4));
  }
  asm volatile("ld.global.nc.v4.u32 {%0, %1, %2, %3}, [%4];" : "=r"(U.s4.x), "=r"(U.s4.y), "=r"(U.s4.z), "=r"(U.s4.w) : "l"(a.ks + 8 * ch));
  asm volatile("ld.global.nc.v4.u32 {%0, %1, %2, %3}, [%4];" : "=r"(U.z4.x), "=r"(U.z4.y), "=r"(U.z4.z), "=r"(U.z4.w) : "l"(a.kz + 8 * ch));
}
__device__ __forceinline__ void k0_store(const K0Unit& U, int tok0, int lane, uint32_t img, uint32_t peer_img, uint32_t peer_bar) {
  const int ch = lane & 15;
#pragma unroll
  for (int it = 0; it < 4; it++) {
    const int t = tok0 + (lane >> 4) + it * 2;
    const int x[8] = {U.v[it][0].x, U.v[it][0].y, U.v[it][0].z, U.v[it][0].w, U.v[it][1].x, U.v[it][1].y, U.v[it][1].z, U.v[it][1].w};
    const uint32_t sc[4] = {U.s4.x, U.s4.y, U.s4.z, U.s4.w}, zr[4] = {U.z4.x, U.z4.y, U.z4.z, U.z4.w};
    uint32_t w[4];
#pragma unroll
    for (int c = 0; c < 4; c++) {
      uint32_t y = pack_bf16(__int2float_rn(x[2 * c]), __int2float_rn(x[2 * c + 1]));
      y = bmul2(bsub2(y, zr[c]), sc[c]);
      w[c] = bfma2(y, KSCALE_HI2, bmul2(y, KSCALE_LO2));
    }
    const uint32_t off = (ch >> 3) * 16384 + t * 128 + (((ch & 7) ^ (t & 7)) << 4);
    asm volatile("st.shared.v4.b32 [%0], {%1, %2, %3, %4};" ::"r"(img + off), "r"(w[0]), "r"(w[1]), "r"(w[2]), "r"(w[3]) : "memory");
    asm volatile("st.async.weak.shared::cluster.mbarrier::complete_tx::bytes.v4.b32 [%0], {%1, %2, %3, %4}, [%5];"
                 ::"r"(peer_img + off), "r"(w[0]), "r"(w[1]), "r"(w[2]), "r"(w[3]), "r"(peer_bar) : "memory");
  }
}
__device__ __forceinline__ uint32_t warp_max_bits(uint32_t m2) {
  return __reduce_max_sync(0xffffffffu, max((m2 << 16) & 0x7fff0000u, m2 & 0x7fff0000u));
}
__device__ __forceinline__ void publish(int head, uint32_t rows, uint32_t vbest) {
  const unsigned long long add = rows | (vbest > VMAX_HI ? 1ull << 16 : 0ull) | (vbest >= VMAX_LO ? 1ull << 32 : 0ull);
  asm volatile("fence.proxy.async.global;" ::: "memory");
  asm volatile("fence.acq_rel.gpu;" ::: "memory");
#pragma unroll
  for (int c = 0; c < NREP; c++)
    asm volatile("red.relaxed.gpu.global.add.u64 [%0], %1;" ::"l"(g_ready + (head * NREP + c) * RSTRIDE), "l"(add) : "memory");
}
__device__ __forceinline__ unsigned long long ld_acquire(const unsigned long long* p) {
  unsigned long long v; asm volatile("ld.acquire.gpu.global.u64 %0, [%1];" : "=l"(v) : "l"(p) : "memory"); return v;
}

__device__ __forceinline__ void mbar_init(uint32_t bar, uint32_t count) {
  asm volatile("mbarrier.init.shared::cta.b64 [%0], %1;" ::"r"(bar), "r"(count) : "memory");
}
__device__ __forceinline__ void mbar_expect_tx(uint32_t bar, uint32_t bytes) {
  asm volatile("mbarrier.arrive.expect_tx.shared::cta.b64 _, [%0], %1;" ::"r"(bar), "r"(bytes) : "memory");
}
__device__ __forceinline__ void mbar_arrive(uint32_t bar) {
  asm volatile("mbarrier.arrive.shared::cta.b64 _, [%0];" ::"r"(bar) : "memory");
}
__device__ __forceinline__ void mbar_wait(uint32_t bar, uint32_t parity) {
  asm volatile(
      "{\n"
      ".reg .pred p;\n"
      "WAIT_LOOP:\n"
      "mbarrier.try_wait.parity.shared::cta.b64 p, [%0], %1;\n"
      "@p bra.uni WAIT_DONE;\n"
      "bra.uni WAIT_LOOP;\n"
      "WAIT_DONE:\n"
      "}\n" ::"r"(bar), "r"(parity) : "memory");
}
__device__ __forceinline__ void bulk_load_mc(uint32_t dst, const void* src, uint32_t bytes, uint32_t bar) {
  asm volatile("cp.async.bulk.shared::cluster.global.mbarrier::complete_tx::bytes.multicast::cluster [%0], [%1], %2, [%3], %4;"
               ::"r"(dst), "l"(src), "r"(bytes), "r"(bar), "h"((uint16_t)3) : "memory");
}
__device__ __forceinline__ void mbar_arrive_cluster(uint32_t bar) {
  asm volatile("mbarrier.arrive.shared::cluster.b64 _, [%0];" ::"r"(bar) : "memory");
}
__device__ __forceinline__ void cluster_arrive() { asm volatile("barrier.cluster.arrive.relaxed.aligned;" ::: "memory"); }
__device__ __forceinline__ void cluster_wait() { asm volatile("barrier.cluster.wait.acquire.aligned;" ::: "memory"); }
__device__ __forceinline__ void wg_fence() { asm volatile("wgmma.fence.sync.aligned;" ::: "memory"); }
__device__ __forceinline__ void wg_commit() { asm volatile("wgmma.commit_group.sync.aligned;" ::: "memory"); }
template <int N> __device__ __forceinline__ void wg_wait() { asm volatile("wgmma.wait_group.sync.aligned %0;" ::"n"(N) : "memory"); }
__device__ __forceinline__ void bar_sync(int id) { asm volatile("bar.sync %0, 256;" ::"r"(id) : "memory"); }
__device__ __forceinline__ void bar_arrive(int id) { asm volatile("bar.arrive %0, 256;" ::"r"(id) : "memory"); }

#define A8(d, o) "+f"(d[o + 0]), "+f"(d[o + 1]), "+f"(d[o + 2]), "+f"(d[o + 3]), "+f"(d[o + 4]), "+f"(d[o + 5]), "+f"(d[o + 6]), "+f"(d[o + 7])
#define ACC64(d) A8(d, 0), A8(d, 8), A8(d, 16), A8(d, 24), A8(d, 32), A8(d, 40), A8(d, 48), A8(d, 56)
#define REGS64                                                                                \
  "{%0, %1, %2, %3, %4, %5, %6, %7, %8, %9, %10, %11, %12, %13, %14, %15, "                   \
  "%16, %17, %18, %19, %20, %21, %22, %23, %24, %25, %26, %27, %28, %29, %30, %31, "          \
  "%32, %33, %34, %35, %36, %37, %38, %39, %40, %41, %42, %43, %44, %45, %46, %47, "          \
  "%48, %49, %50, %51, %52, %53, %54, %55, %56, %57, %58, %59, %60, %61, %62, %63}"

template <int TB>
__device__ __forceinline__ void mma_rs(float (&d)[64], uint32_t a0, uint32_t a1, uint32_t a2, uint32_t a3,
                                       uint64_t desc, int scale_d) {
  asm volatile(
      "{\n.reg .pred p;\nsetp.ne.b32 p, %69, 0;\n"
      "wgmma.mma_async.sync.aligned.m64n128k16.f32.bf16.bf16 " REGS64
      ", {%64, %65, %66, %67}, %68, p, 1, 1, %70;\n}\n"
      : ACC64(d)
      : "r"(a0), "r"(a1), "r"(a2), "r"(a3), "l"(desc), "r"(scale_d), "n"(TB));
}
__device__ __forceinline__ void fence_regs(float (&d)[64]) {
#pragma unroll
  for (int i = 0; i < 64; i++) asm volatile("" : "+f"(d[i])::"memory");
}
__device__ __forceinline__ void fence_regs_u(uint32_t (&d)[32]) {
#pragma unroll
  for (int i = 0; i < 32; i++) asm volatile("" : "+r"(d[i])::"memory");
}

__device__ __forceinline__ uint64_t make_desc(uint32_t addr, uint32_t lbo_bytes) {
  return (uint64_t)((addr & 0x3FFFF) >> 4) | ((uint64_t)(lbo_bytes >> 4) << 16) | ((uint64_t)(1024 >> 4) << 32) |
         ((uint64_t)1 << 62);
}

__device__ __forceinline__ void issue_qk(float (&S)[64], const uint32_t (&Q)[32], uint32_t kaddr) {
  const uint64_t d0 = make_desc(kaddr, 16);
#pragma unroll
  for (int kk = 0; kk < 8; kk++) {
    const uint64_t off = (uint64_t)(((kk >> 2) * 16384 + (kk & 3) * 32) >> 4);
    mma_rs<0>(S, Q[kk * 4 + 0], Q[kk * 4 + 1], Q[kk * 4 + 2], Q[kk * 4 + 3], d0 + off, kk != 0);
  }
}
__device__ __forceinline__ void issue_pv(float (&O)[64], const uint32_t (&P)[32], uint32_t vaddr, int acc) {
  const uint64_t d0 = make_desc(vaddr, 16384);
#pragma unroll
  for (int kk = 0; kk < 8; kk++)
    mma_rs<1>(O, P[kk * 4 + 0], P[kk * 4 + 1], P[kk * 4 + 2], P[kk * 4 + 3], d0 + (uint64_t)((kk * 2048) >> 4),
              kk == 0 ? acc : 1);
}

__device__ __forceinline__ void tma_load_2d(uint32_t dst, const CUtensorMap* tm, int c0, int c1, uint32_t bar) {
  asm volatile("cp.async.bulk.tensor.2d.shared::cluster.global.mbarrier::complete_tx::bytes [%0], [%1, {%3, %4}], [%2];"
               ::"r"(dst), "l"(tm), "r"(bar), "r"(c0), "r"(c1) : "memory");
}
__device__ __forceinline__ void load_q(uint32_t (&Q)[32], uint32_t qaddr) {
#pragma unroll
  for (int kk = 0; kk < 8; kk++)
    asm volatile("ldmatrix.sync.aligned.m8n8.x4.shared.b16 {%0, %1, %2, %3}, [%4];"
                 : "=r"(Q[kk * 4 + 0]), "=r"(Q[kk * 4 + 1]), "=r"(Q[kk * 4 + 2]), "=r"(Q[kk * 4 + 3])
                 : "r"((qaddr ^ ((kk & 3) << 5)) + (kk >> 2) * 16384) : "memory");
}

__device__ __forceinline__ void tma_store_2d(const CUtensorMap* tm, uint32_t src, int c0, int c1) {
  asm volatile("cp.async.bulk.tensor.2d.global.shared::cta.bulk_group [%0, {%2, %3}], [%1];"
               ::"l"(tm), "r"(src), "r"(c0), "r"(c1) : "memory");
}
__device__ __forceinline__ void cluster_arrive_lane() { asm volatile("barrier.cluster.arrive.relaxed;" ::: "memory"); }
__device__ __forceinline__ void cluster_wait_lane() { asm volatile("barrier.cluster.wait.acquire;" ::: "memory"); }

template <int N> struct IC { static constexpr int value = N; };

__global__ void __cluster_dims__(2, 1, 1) __launch_bounds__(384, 1)
attn_kernel(const __grid_constant__ CUtensorMap tmap_q, const __grid_constant__ CUtensorMap tmap_o,
            const __grid_constant__ DeqArgs deq, int first_helper) {
  extern __shared__ uint8_t smem_raw[];
  const uint32_t smem_base = (smem_u32(smem_raw) + 1023u) & ~1023u;
  const uint32_t q_smem = smem_base + NSLOT * TILE_BYTES;
  const uint32_t bar_full = q_smem + TILE_BYTES;
  const uint32_t bar_empty = bar_full + 8 * NSLOT;
  const uint32_t bar_peer = bar_empty + 8 * NSLOT;
  const uint32_t bar_qfull = bar_peer + 8 * NSLOT;
  const uint32_t bar_qempty = bar_qfull + 16;
  const uint32_t bar_k0 = bar_qempty + 8;
  const uint32_t bar_pok = bar_k0 + 8;
  const uint32_t redo_smem = bar_pok + 8;
  const uint32_t red_smem = bar_full + 512;
  const int tid = threadIdx.x;
  const int warp = __shfl_sync(0xffffffffu, tid >> 5, 0);
  const int lane = tid & 31;
  if (warp == 8) {
    if (lane == 0) {
#pragma unroll
      for (int s = 0; s < NSLOT; s++) {
        mbar_init(bar_full + 8 * s, 1);
        mbar_init(bar_empty + 8 * s, 8);
        mbar_init(bar_peer + 8 * s, 1);
      }
      mbar_init(bar_qfull, 1);
      mbar_init(bar_qfull + 8, 1);
      mbar_init(bar_qempty, 8);
      mbar_init(bar_k0, 9);
      mbar_init(bar_pok, 1);
      asm volatile("st.shared.u32 [%0], %1;" ::"r"(redo_smem), "r"(0) : "memory");
      mbar_expect_tx(bar_k0, TILE_BYTES / 2);
      asm volatile("fence.mbarrier_init.release.cluster;" ::: "memory");
    }
    __syncwarp();
    asm volatile("bar.arrive 3, 64;" ::: "memory");
  }
  cluster_arrive();
  const int grid = (int)gridDim.x;
  const bool helper = (int)blockIdx.x >= first_helper;
  const bool self0 = !helper && (int)blockIdx.x < TILES_PER_KVH;
  const uint32_t rank = blockIdx.x & 1;
  auto load_q_half = [&](int r, int w) {
    const int row = ((int)blockIdx.x + r * grid) * TILE_M + 64 * w;
    mbar_expect_tx(bar_qfull + 8 * w, TILE_BYTES / 2);
    tma_load_2d(q_smem + w * 8192, &tmap_q, 0, row, bar_qfull + 8 * w);
    tma_load_2d(q_smem + w * 8192 + 16384, &tmap_q, 64, row, bar_qfull + 8 * w);
  };
  K0Unit k0u;
  const int k0_tok = (int)rank * 64 + warp * 8;
  Unit4 U;
  const int x0 = ((int)blockIdx.x - first_helper) * 12 + warp;
  auto stage_tok = [&](int st, int x) { return (3 * st + (x >> 6) + 1 - ((x >> 5) & 1)) * BLK + (x & 31) * 4; };
  if (helper && x0 < STAGE_ROWS / 4) unit4_load(deq, (x0 >> 5) & 1, stage_tok(0, x0), lane, U);
  if (warp < 8) {
    if (self0) k0_load(deq, k0_tok, lane, k0u);
  } else if (warp == 9) {
    if (lane == 0) asm volatile("prefetch.tensormap [%0];" ::"l"(&tmap_q) : "memory");
    asm volatile("bar.sync 3, 64;" ::: "memory");
    if (self0 && lane == 0) {
      { long long t0 = clock64(); while (clock64() - t0 < QDELAY) {} }
      load_q_half(0, 0);
      { long long t0 = clock64(); while (clock64() - t0 < QDELAY2) {} }
      load_q_half(0, 1);
    }
    __syncwarp();
  } else if (tid == 352) {
    asm volatile("prefetch.tensormap [%0];" ::"l"(&tmap_o) : "memory");
  }
  __syncwarp();

  if (helper) {
    const int nh = grid - first_helper, hb = (int)blockIdx.x - first_helper;
    auto publish_all = [&](uint32_t red) {
      uint32_t v = 0, n = 0, hd = 0, pad;
      if (lane < 12) asm volatile("ld.shared.v4.u32 {%0, %1, %2, %3}, [%4];" : "=r"(v), "=r"(n), "=r"(hd), "=r"(pad) : "r"(red + 16 * lane) : "memory");
      unsigned todo = __ballot_sync(0xffffffffu, n != 0);
      while (todo) {
        const uint32_t h = __shfl_sync(0xffffffffu, hd, __ffs(todo) - 1);
        const bool m = n != 0 && hd == h;
        const uint32_t hv = __reduce_max_sync(0xffffffffu, m ? v : 0u);
        const uint32_t hn = __reduce_add_sync(0xffffffffu, m ? n : 0u);
        if (lane == 0) publish(h, hn, hv);
        todo &= ~__ballot_sync(0xffffffffu, m);
      }
      __syncwarp();
    };
    int buf = 0;
#pragma unroll 1
    for (int st = 0; st < NSTAGE; st++, buf ^= 1) {
      uint32_t vb2 = 0, rows = 0;
#pragma unroll 1
      for (int x = x0; x < STAGE_ROWS / 4; x += nh * 12) {
        if (st != 0 || x != x0) unit4_load(deq, (x >> 5) & 1, stage_tok(st, x), lane, U);
        unit4_store(U, (x >> 5) & 1, stage_tok(st, x), lane, vb2);
        rows += 4;
      }
      const uint32_t vbest = warp_max_bits(vb2);
      const uint32_t red = red_smem + buf * 192;
      if (lane == 0) asm volatile("st.shared.v4.u32 [%0], {%1, %2, %3, %3};" ::"r"(red + 16 * warp), "r"(vbest), "r"(rows), "r"(HKV + st) : "memory");
      __syncthreads();
      if (warp == 10 + buf) {
        publish_all(red);
      }
      if (st == 0) __syncthreads();
    }
    constexpr int UPH = 2 * SEQ / 16;
#pragma unroll 1
    for (int u0 = 0; u0 < (HKV - 1) * UPH; u0 += 12 * nh, buf ^= 1) {
      const int u = u0 + warp * nh + hb;
      uint32_t vb2 = 0, rows = 0;
      const int head = 1 + u / UPH;
      if (u < (HKV - 1) * UPH) {
        const int w = u % UPH;
        dequant_unit<8>(deq, head, w >= UPH / 2, (w & (UPH / 2 - 1)) * 16, lane, vb2);
        rows = 16;
      }
      const uint32_t vbest = warp_max_bits(vb2);
      const uint32_t red = red_smem + buf * 192;
      if (lane == 0) asm volatile("st.shared.v4.u32 [%0], {%1, %2, %3, %3};" ::"r"(red + 16 * warp), "r"(vbest), "r"(rows), "r"(head) : "memory");
      __syncthreads();
      if (warp == 10 + buf) publish_all(red);
    }
    __syncthreads();
  }

  const int ntile = (NTILES - (int)blockIdx.x + grid - 1) / grid;
  const int total = ntile * NBLK;
  auto mark_redo = [&](int r) {
    uint32_t peer_redo;
    asm volatile("mapa.shared::cluster.u32 %0, %1, %2;" : "=r"(peer_redo) : "r"(redo_smem), "r"(rank ^ 1));
    asm volatile("{\n.reg .pred p;\nPOK_LOOP:\nmbarrier.try_wait.parity.acquire.cluster.shared::cta.b64 p, [%0], 0;\n"
                 "@p bra.uni POK_DONE;\nbra.uni POK_LOOP;\nPOK_DONE:\n}\n" ::"r"(bar_pok) : "memory");
    asm volatile("red.relaxed.cluster.shared::cta.or.b32 [%0], %1;" ::"r"(redo_smem), "r"(1u << (r & 31)) : "memory");
    asm volatile("red.relaxed.cluster.shared::cluster.or.b32 [%0], %1;" ::"r"(peer_redo), "r"(1u << (r & 31)) : "memory");
    asm volatile("fence.acq_rel.cluster;" ::: "memory");
  };
  auto read_redo = [&]() {
    uint32_t v; asm volatile("ld.volatile.shared.u32 %0, [%1];" : "=r"(v) : "r"(redo_smem) : "memory"); return v;
  };

  if (warp >= 8) {
    asm volatile("setmaxnreg.dec.sync.aligned.u32 56;");
    if (!helper && warp >= 9) {
      { long long t0 = clock64(); while (clock64() - t0 < RDELAY) {} }
      uint32_t vb2 = 0, rows = 0;
#pragma unroll 1
      for (int x = (int)blockIdx.x * 3 + warp - 9; x < HEAD0_REST / 4; x += first_helper * 3) {
        const int b = x >> 5, isV = b >= 10;
        dequant_unit<2>(deq, 0, isV, (isV ? b - 4 : (b ? b + 6 : 0)) * BLK + (x & 31) * 4, lane, vb2);
        rows += 4;
      }
      const uint32_t vbest = warp_max_bits(vb2);
      __syncwarp();
      if (lane == 0 && rows) publish(0, rows, vbest);
      __syncwarp();
    }
    cluster_wait();
    if (tid != 256) return;
    auto load_qtile = [&](int r) { load_q_half(r, 0); load_q_half(r, 1); };
    auto wait_rows = [&](int c, uint32_t n) {
      unsigned long long v;
      while (((v = ld_acquire(g_ready + (c * NREP + (((int)blockIdx.x >> 1) & (NREP - 1))) * RSTRIDE)) & 0xffff) < n) {}
      return v >> 16;
    };
    auto check_v = [&](unsigned long long f, int r) { if ((f & 0xffff) != 0 || (f >> 16) == 0) mark_redo(r); };
    auto wait_head = [&](int r) {
      const int h = ((int)blockIdx.x + r * grid) / TILES_PER_KVH;
      unsigned long long f = wait_rows(h, h ? 2 * SEQ : HEAD0_REST);
      if (h == 0) { f |= wait_rows(HKV, STAGE_ROWS); f |= wait_rows(HKV + 1, STAGE_ROWS); }
      return f;
    };
    unsigned long long vflags = 0;
    if (self0) {
      mbar_arrive(bar_full);
      vflags = wait_rows(HKV, STAGE_ROWS);
    } else {
      load_qtile(0);
      vflags = wait_head(0);
    }
    int slot = 0;
    uint32_t phase = 1;
    const uint32_t half = (blockIdx.x & 1) * (TILE_BYTES / 2);
    uint32_t peer_c;
    asm volatile("mapa.shared::cluster.u32 %0, %1, %2;" : "=r"(peer_c) : "r"(bar_peer), "r"((blockIdx.x & 1) ^ 1));
    bool warm = false;
    const uint8_t* kbase = g_kv;
    const uint8_t* vbase = g_kv + (size_t)HKV * NBLK * TILE_BYTES;
    auto load = [&](const uint8_t* base, int it) {
      const int u = (int)blockIdx.x + (it >> 4) * grid;
      const uint8_t* src = base + (size_t)((u / TILES_PER_KVH) * NBLK + (it & 15)) * TILE_BYTES;
      mbar_wait(bar_empty + 8 * slot, phase);
      if (warm) mbar_arrive_cluster(peer_c + 8 * slot);
      mbar_wait(bar_peer + 8 * slot, phase);
      mbar_expect_tx(bar_full + 8 * slot, TILE_BYTES);
      bulk_load_mc(smem_base + slot * TILE_BYTES + half, src + half, TILE_BYTES / 2, bar_full + 8 * slot);
      if (++slot == NSLOT) { slot = 0; phase ^= 1; warm = true; }
    };
    auto retire = [&]() {
      uint32_t n;
      asm volatile("atom.acq_rel.gpu.global.add.u32 %0, [%1], 1;" : "=r"(n) : "l"(&g_done) : "memory");
      if (n == (uint32_t)grid - 1) {
#pragma unroll
        for (int h = 0; h < (HKV + NSTAGE) * NREP; h++) g_ready[h * RSTRIDE] = 0;
        g_done = 0;
      }
    };
    if (self0) slot = 1;
    else load(kbase, 0);
    for (int it = 0; it < total - 1; it++) {
      if (it == 3 && self0) vflags |= wait_rows(HKV + 1, STAGE_ROWS);
      if (it == 6) {
        uint32_t peer_pok;
        asm volatile("mapa.shared::cluster.u32 %0, %1, %2;" : "=r"(peer_pok) : "r"(bar_pok), "r"(rank ^ 1));
        asm volatile("mbarrier.arrive.release.cluster.shared::cluster.b64 _, [%0];" ::"r"(peer_pok) : "memory");
        if (self0) vflags |= wait_rows(0, HEAD0_REST);
        check_v(vflags, 0);
        if (ntile == 1) retire();
      }
      if ((it & 15) == 10 && (it >> 4) + 1 < ntile) {
        check_v(wait_head((it >> 4) + 1), (it >> 4) + 1);
        if ((it >> 4) + 2 == ntile) retire();
        mbar_wait(bar_qempty, (it >> 4) & 1);
        load_qtile((it >> 4) + 1);
      }
      load(kbase, it + 1);
      load(vbase, it);
    }
    load(vbase, total - 1);
    cluster_arrive_lane();
    cluster_wait_lane();
    const uint32_t todo = read_redo();
    if (todo) {
      for (int r = 0, k = ntile; r < ntile; r++) {
        if (!((todo >> (r & 31)) & 1)) continue;
        mbar_wait(bar_qempty, k & 1);
        k++;
        load_qtile(r);
        for (int j = 0; j < NBLK; j++) {
          load(kbase, r * NBLK + j);
          load(vbase, r * NBLK + j);
        }
      }
      cluster_arrive_lane();
      cluster_wait_lane();
    }
  } else {
    cluster_wait();
    if (self0) {
      uint32_t peer_img, peer_bar;
      asm volatile("mapa.shared::cluster.u32 %0, %1, %2;" : "=r"(peer_img) : "r"(smem_base), "r"(rank ^ 1));
      asm volatile("mapa.shared::cluster.u32 %0, %1, %2;" : "=r"(peer_bar) : "r"(bar_k0), "r"(rank ^ 1));
      k0_store(k0u, k0_tok, lane, smem_base, peer_img, peer_bar);
      __syncwarp();
      if (lane == 0) mbar_arrive(bar_k0);
    }
    asm volatile("setmaxnreg.inc.sync.aligned.u32 224;");
    const int wg = warp >> 2;
    const uint32_t bar_qf = bar_qfull + 8 * wg;
    const int row0 = wg * 64 + (warp & 3) * 16;
    int orow = (int)blockIdx.x * TILE_M + row0;
    const uint32_t q_lane = q_smem + (row0 + (lane & 15)) * 128 + (((lane >> 4) ^ (lane & 7)) << 4);

    float S[64], O[64];
    uint32_t P[32], Q[32];
    float l0 = 0.f, l1 = 0.f;
    float lf0 = 0.f, lf1 = 0.f;
    int slot = 0;
    uint32_t phase = 0;
    auto advance = [&]() { if (++slot == NSLOT) { slot = 0; phase ^= 1; } };

    mbar_wait(bar_qf, 0);
    load_q(Q, q_lane);
    __syncwarp();
    if (lane == 0) mbar_arrive(bar_qempty);

    auto softmax = [&]() {
#pragma unroll
      for (int i = 0; i < 64; i += 4) {
        S[i + 0] = ex2(S[i + 0]); S[i + 1] = ex2(S[i + 1]);
        S[i + 2] = ex2(S[i + 2]); S[i + 3] = ex2(S[i + 3]);
        l0 += S[i + 0]; l1 += S[i + 2];
        l0 += S[i + 1]; l1 += S[i + 3];
      }
    };
    auto softmax_part = [&](auto lo_c, auto hi_c) {
#pragma unroll
      for (int i = decltype(lo_c)::value; i < decltype(hi_c)::value; i += 4) {
        S[i + 0] = ex2(S[i + 0]); S[i + 1] = ex2(S[i + 1]);
        S[i + 2] = ex2(S[i + 2]); S[i + 3] = ex2(S[i + 3]);
        l0 += S[i + 0]; l1 += S[i + 2];
        l0 += S[i + 1]; l1 += S[i + 3];
      }
    };
    auto pack_p = [&]() {
#pragma unroll
      for (int i = 0; i < 32; i++) P[i] = pack_bf16(S[2 * i], S[2 * i + 1]);
    };
    auto row_sums = [&](float& e0, float& e1) {
      e0 += __shfl_xor_sync(0xffffffffu, e0, 1);
      e1 += __shfl_xor_sync(0xffffffffu, e1, 1);
      e0 += __shfl_xor_sync(0xffffffffu, e0, 2);
      e1 += __shfl_xor_sync(0xffffffffu, e1, 2);
    };
    auto recips = [&](float& e0, float& e1) {
      asm("rcp.approx.ftz.f32 %0, %0;" : "+f"(e0));
      asm("rcp.approx.ftz.f32 %0, %0;" : "+f"(e1));
    };
    auto finish_l = [&](float& e0, float& e1, int r) {
      row_sums(e0, e1);
      const bool ok = e0 >= LSUM_LO && e0 <= LSUM_HI && e1 >= LSUM_LO && e1 <= LSUM_HI;
      if (!ok) mark_redo(r);
      recips(e0, e1);
    };
    auto epilogue = [&](int h, float r0, float r1) {
#pragma unroll
      for (int kk = 0; kk < 4; kk++) {
        const float* o = &O[32 * h + 8 * kk];
        const uint32_t a0 = pack_bf16(o[0] * r0, o[1] * r0), a1 = pack_bf16(o[2] * r1, o[3] * r1);
        const uint32_t a2 = pack_bf16(o[4] * r0, o[5] * r0), a3 = pack_bf16(o[6] * r1, o[7] * r1);
        asm volatile("stmatrix.sync.aligned.m8n8.x4.shared.b16 [%0], {%1, %2, %3, %4};"
                     ::"r"((q_lane ^ (kk << 5)) + h * 16384), "r"(a0), "r"(a1), "r"(a2), "r"(a3) : "memory");
      }
    };
    auto store_out = [&](int row, int h0, int h1) {
      asm volatile("fence.proxy.async.shared::cta;" ::: "memory");
      __syncwarp();
      if (lane == 0) {
        for (int h = h0; h < h1; h++) tma_store_2d(&tmap_o, q_smem + h * 16384 + row0 * 128, 64 * h, row);
        asm volatile("cp.async.bulk.commit_group;" ::: "memory");
      }
    };

    const uint32_t stage_lane = q_smem + (row0 + (lane >> 3)) * 128;
    auto direct_ld = [&](uint4 (&v)[4], int h) {
      __syncwarp();
#pragma unroll
      for (int i = 0; i < 4; i++)
        asm volatile("ld.shared.v4.u32 {%0, %1, %2, %3}, [%4];" : "=r"(v[i].x), "=r"(v[i].y), "=r"(v[i].z), "=r"(v[i].w)
                     : "r"(stage_lane + h * 16384 + i * 512 + (((lane & 7) ^ ((i * 4 + (lane >> 3)) & 7)) << 4)) : "memory");
    };
    auto direct_st = [&](const uint4 (&v)[4], uint8_t* dst, int h) {
#pragma unroll
      for (int i = 0; i < 4; i++)
        asm volatile("st.global.v4.u32 [%0], {%1, %2, %3, %4};" ::"l"(dst + i * 4 * DH * 2 + h * 128), "r"(v[i].x), "r"(v[i].y), "r"(v[i].z), "r"(v[i].w) : "memory");
    };
    auto direct_dst = [&](int row) { return reinterpret_cast<uint8_t*>(deq.out + (size_t)(row + (lane >> 3)) * DH + (lane & 7) * 8); };

    if (wg == 1) bar_arrive(1);
    mbar_wait(bar_full + 8 * slot, phase);
    if (self0) {
      mbar_wait(bar_k0, 0);
      asm volatile("fence.proxy.async.shared::cta;" ::: "memory");
    }
    wg_fence();
    issue_qk(S, Q, smem_base + slot * TILE_BYTES);
    wg_commit();
    wg_wait<0>();
    fence_regs(S);
    if (lane == 0) mbar_arrive(bar_empty + 8 * slot);
    advance();
    softmax();
    pack_p();

    for (int it = 0; it < total - 1; it++) {
      const int j = it & 15;
      const int kslot = slot;
      const uint32_t kphase = phase;
      advance();
      const int vslot = slot;
      const uint32_t vphase = phase;
      advance();

      if (j == 15) {
        mbar_wait(bar_qf, ((it >> 4) + 1) & 1);
        load_q(Q, q_lane);
      }
      bar_sync(1 + wg);
      mbar_wait(bar_full + 8 * kslot, kphase);
      if (it != 0) mbar_wait(bar_full + 8 * vslot, vphase);
      wg_fence();
      issue_qk(S, Q, smem_base + kslot * TILE_BYTES);
      wg_commit();
      if (it == 0) mbar_wait(bar_full + 8 * vslot, vphase);
      if (j == 15) {
        lf0 = l0; lf1 = l1;
        finish_l(lf0, lf1, it >> 4);
        l0 = 0.f; l1 = 0.f;
      } else if (j == 0 && it != 0) {
        epilogue(1, lf0, lf1);
        store_out(orow, 0, 2);
        orow += grid * TILE_M;
      } else if (j == 2 && it > 16) {
        if (lane == 0) {
          asm volatile("cp.async.bulk.wait_group.read 0;" ::: "memory");
          mbar_arrive(bar_qempty);
        }
        __syncwarp();
      }
      wg_fence();
      issue_pv(O, P, smem_base + vslot * TILE_BYTES, j != 0);
      wg_commit();
      bar_arrive(2 - wg);

      wg_wait<1>();
      fence_regs(S);
      if (lane == 0) mbar_arrive(bar_empty + 8 * kslot);
      if (first_helper >= 0) softmax_part(IC<0>{}, IC<NSPLIT>{});
      wg_wait<0>();
      fence_regs(O);
      fence_regs_u(P);
      if (lane == 0) mbar_arrive(bar_empty + 8 * vslot);
      if (first_helper > -7) {
        softmax_part(IC<NSPLIT>{}, IC<64>{});
        pack_p();
      }
      if (j == 15) epilogue(0, lf0, lf1);
    }
    bar_sync(1 + wg);
    mbar_wait(bar_full + 8 * slot, phase);
    wg_fence();
    issue_pv(O, P, smem_base + slot * TILE_BYTES, 1);
    wg_commit();
    if (wg == 0) bar_arrive(2);
    finish_l(l0, l1, ntile - 1);
    cluster_arrive();
    if (lane == 0) asm volatile("cp.async.bulk.wait_group.read 0;" ::: "memory");
    __syncwarp();
    {
      uint8_t* dst = direct_dst(orow);
      asm volatile("" : "+l"(dst));
      uint4 v[4];
      wg_wait<0>();
      fence_regs(O);
      if (lane == 0) mbar_arrive(bar_empty + 8 * slot);
      advance();
      epilogue(0, l0, l1);
      direct_ld(v, 0);
      epilogue(1, l0, l1);
      direct_st(v, dst, 0);
      direct_ld(v, 1);
      direct_st(v, dst, 1);
    }
    __syncwarp();
    cluster_wait();
    const uint32_t todo = read_redo();
    if (todo) {
#pragma unroll 1
      for (int r = 0, k = ntile; r < ntile; r++) {
        if (!((todo >> (r & 31)) & 1)) continue;
        asm volatile("fence.proxy.async.shared::cta;" ::: "memory");
        __syncwarp();
        if (lane == 0) {
          asm volatile("cp.async.bulk.wait_group 0;" ::: "memory");
          mbar_arrive(bar_qempty);
        }
        __syncwarp();
        mbar_wait(bar_qf, k & 1);
        k++;
        float m0 = -INFINITY, m1 = -INFINITY;
        l0 = 0.f; l1 = 0.f;
#pragma unroll 1
        for (int j = 0; j < NBLK; j++) {
          load_q(Q, q_lane);
          mbar_wait(bar_full + 8 * slot, phase);
          wg_fence();
          issue_qk(S, Q, smem_base + slot * TILE_BYTES);
          wg_commit();
          wg_wait<0>();
          fence_regs(S);
          if (lane == 0) mbar_arrive(bar_empty + 8 * slot);
          advance();
          float x0 = fmaxf(S[0], S[1]), x1 = fmaxf(S[2], S[3]);
#pragma unroll
          for (int i = 4; i < 64; i += 4) {
            x0 = fmaxf(x0, fmaxf(S[i + 0], S[i + 1]));
            x1 = fmaxf(x1, fmaxf(S[i + 2], S[i + 3]));
          }
          x0 = fmaxf(x0, __shfl_xor_sync(0xffffffffu, x0, 1));
          x1 = fmaxf(x1, __shfl_xor_sync(0xffffffffu, x1, 1));
          x0 = fmaxf(x0, __shfl_xor_sync(0xffffffffu, x0, 2));
          x1 = fmaxf(x1, __shfl_xor_sync(0xffffffffu, x1, 2));
          const float n0 = fmaxf(m0, x0), n1 = fmaxf(m1, x1);
          const float al0 = (n0 == -INFINITY) ? 1.f : ex2(m0 - n0);
          const float al1 = (n1 == -INFINITY) ? 1.f : ex2(m1 - n1);
          m0 = n0; m1 = n1;
          l0 *= al0; l1 *= al1;
          const float s0 = (m0 == -INFINITY) ? 0.f : m0, s1 = (m1 == -INFINITY) ? 0.f : m1;
#pragma unroll
          for (int i = 0; i < 64; i += 4) {
            S[i + 0] -= s0; S[i + 1] -= s0; S[i + 2] -= s1; S[i + 3] -= s1;
          }
          softmax();
          if (j != 0) {
#pragma unroll
            for (int i = 0; i < 64; i += 4) {
              O[i + 0] *= al0; O[i + 1] *= al0; O[i + 2] *= al1; O[i + 3] *= al1;
            }
          }
          pack_p();
          mbar_wait(bar_full + 8 * slot, phase);
          wg_fence();
          issue_pv(O, P, smem_base + slot * TILE_BYTES, j != 0);
          wg_commit();
          wg_wait<0>();
          fence_regs(O);
          fence_regs_u(P);
          if (lane == 0) mbar_arrive(bar_empty + 8 * slot);
          advance();
        }
        row_sums(l0, l1);
        recips(l0, l1);
        epilogue(0, l0, l1);
        epilogue(1, l0, l1);
        {
          uint4 v[4];
          uint8_t* dst2 = direct_dst(((int)blockIdx.x + r * grid) * TILE_M + row0);
          direct_ld(v, 0);
          direct_st(v, dst2, 0);
          direct_ld(v, 1);
          direct_st(v, dst2, 1);
        }
        __syncwarp();
      }
      if (lane == 0) asm volatile("cp.async.bulk.wait_group.read 0;" ::: "memory");
      __syncwarp();
      cluster_arrive();
      cluster_wait();
    }
  }
}

}

extern "C" void kernel_launch(void* const* d_in, const int* in_sizes, int n_in, void* d_out, int out_size) {
  const __nv_bfloat16* q = (const __nv_bfloat16*)d_in[0];
  const int* qk = (const int*)d_in[1];
  const int* qv = (const int*)d_in[2];
  const __nv_bfloat16* ks = (const __nv_bfloat16*)d_in[3];
  const __nv_bfloat16* kz = (const __nv_bfloat16*)d_in[4];
  const __nv_bfloat16* vs = (const __nv_bfloat16*)d_in[5];
  const __nv_bfloat16* vz = (const __nv_bfloat16*)d_in[6];
  __nv_bfloat16* out = (__nv_bfloat16*)d_out;

  typedef CUresult (*EncodeFn)(CUtensorMap*, CUtensorMapDataType, cuuint32_t, void*, const cuuint64_t*, const cuuint64_t*,
                               const cuuint32_t*, const cuuint32_t*, CUtensorMapInterleave, CUtensorMapSwizzle,
                               CUtensorMapL2promotion, CUtensorMapFloatOOBfill);
  static int num_sms = 0;
  static EncodeFn encode = nullptr;
  if (num_sms == 0) {
    int dev = 0;
    cudaGetDevice(&dev);
    cudaDeviceGetAttribute(&num_sms, cudaDevAttrMultiProcessorCount, dev);
    cudaFuncSetAttribute(attn_kernel, cudaFuncAttributeMaxDynamicSharedMemorySize, SMEM_BYTES);
    void* fn = nullptr;
    cudaDriverEntryPointQueryResult qres;
    cudaGetDriverEntryPoint("cuTensorMapEncodeTiled", &fn, cudaEnableDefault, &qres);
    encode = (EncodeFn)fn;
    cudaLaunchConfig_t cfg = {};
    cfg.gridDim = dim3((unsigned)(num_sms & ~1)); cfg.blockDim = dim3(384); cfg.dynamicSmemBytes = SMEM_BYTES;
    cudaLaunchAttribute attr; attr.id = cudaLaunchAttributeClusterDimension;
    attr.val.clusterDim.x = 2; attr.val.clusterDim.y = 1; attr.val.clusterDim.z = 1;
    cfg.attrs = &attr; cfg.numAttrs = 1;
    int ncl = 0;
    cudaError_t e = cudaOccupancyMaxActiveClusters(&ncl, attn_kernel, &cfg);
    if (e == cudaSuccess && ncl > 0 && 2 * ncl < num_sms) num_sms = 2 * ncl;
    num_sms &= ~1;
  }
  CUtensorMap tmap_q;
  {
    const cuuint64_t gdim[2] = {(cuuint64_t)DH, (cuuint64_t)ROWS};
    const cuuint64_t gstride[1] = {(cuuint64_t)DH * 2};
    const cuuint32_t box[2] = {64, 64};
    const cuuint32_t estride[2] = {1, 1};
    encode(&tmap_q, CU_TENSOR_MAP_DATA_TYPE_BFLOAT16, 2, (void*)q, gdim, gstride, box, estride, CU_TENSOR_MAP_INTERLEAVE_NONE,
           CU_TENSOR_MAP_SWIZZLE_128B, CU_TENSOR_MAP_L2_PROMOTION_L2_256B, CU_TENSOR_MAP_FLOAT_OOB_FILL_NONE);
  }
  CUtensorMap tmap_o;
  {
    const cuuint64_t gdim[2] = {(cuuint64_t)DH, (cuuint64_t)ROWS};
    const cuuint64_t gstride[1] = {(cuuint64_t)DH * 2};
    const cuuint32_t box[2] = {64, 16};
    const cuuint32_t estride[2] = {1, 1};
    encode(&tmap_o, CU_TENSOR_MAP_DATA_TYPE_BFLOAT16, 2, (void*)out, gdim, gstride, box, estride, CU_TENSOR_MAP_INTERLEAVE_NONE,
           CU_TENSOR_MAP_SWIZZLE_128B, CU_TENSOR_MAP_L2_PROMOTION_NONE, CU_TENSOR_MAP_FLOAT_OOB_FILL_NONE);
  }
  DeqArgs deq{qk, qv, ks, kz, vs, vz, out};
  int grid = num_sms < NTILES ? num_sms : NTILES;
  int first_helper = NTILES % grid;
  if (grid - first_helper < 8 || first_helper < 2) first_helper = grid >= 32 ? grid - 16 : (grid / 2 + 1) & ~1;
  attn_kernel<<<grid, 384, SMEM_BYTES>>>(tmap_q, tmap_o, deq, first_helper);
}
```
